```python
import torch

def _softmax(x, axis=-1):
    return torch.softmax(x, dim=axis)
def _gelu(x):
    return torch.nn.functional.gelu(x, approximate="tanh")
def _silu(x):
    return torch.nn.functional.silu(x)
def _sigmoid(x):
    return torch.sigmoid(x)
def _layernorm(x, axis=-1, eps=1e-5):
    m = x.mean(dim=axis, keepdim=True)
    v = x.var(dim=axis, keepdim=True, unbiased=False)
    return (x - m) / torch.sqrt(v + eps)
def _scatter_add(tgt, idx, src, axis=0):
    return tgt.clone().index_add_(axis, idx, src)
def _segment_sum(src, seg, n):
    out = torch.zeros((n,) + src.shape[1:], dtype=src.dtype)
    return out.index_add_(0, seg, src)
def _pad(x, pw):
    flat = tuple(v for pair in reversed(pw) for v in pair)
    return torch.nn.functional.pad(x, flat)

kernel_name = 'standalone__window_attn_swin__vision'

def setup_inputs():

    _w = (lambda a: (lambda t: t.to(torch.bfloat16) if t.is_floating_point() else t)(torch.as_tensor(a)))
    H = W = 512
    C = 192
    ws = 8
    nh = 4
    shift = ws // 2
    coords = torch.stack(torch.meshgrid(torch.arange(ws), torch.arange(ws), indexing='ij'), 0).reshape(2, -1)
    rel = coords[:, :, None] - coords[:, None, :]
    rel[0] += ws - 1
    rel[1] += ws - 1
    rel[0] *= 2 * ws - 1
    rp_idx = rel.sum(0).to(torch.int64)
    img_mask = torch.zeros((1, H, W, 1), dtype=float)
    cnt = 0
    for hs in (slice(0, H - ws), slice(H - ws, H - shift), slice(H - shift, H)):
        for vs in (slice(0, W - ws), slice(W - ws, W - shift), slice(W - shift, W)):
            img_mask[:, hs, vs, :] = cnt
            cnt += 1
    mw = img_mask.reshape(1, H // ws, ws, W // ws, ws, 1).permute(0, 1, 3, 2, 4, 5).reshape(-1, ws * ws)
    am = mw[:, :, None] - mw[:, None, :]
    attn_mask = torch.where(am != 0, -100.0, 0.0).to(float)
    return {
        "x": _w((lambda *s: torch.randn(*s, dtype=torch.bfloat16) * 1.6)(1, H, W, C)),
        "wqkv": _w((lambda *s: torch.randn(*s, dtype=torch.bfloat16) * 1.6)(C, 3 * C) * 0.02),
        "wo": _w((lambda *s: torch.randn(*s, dtype=torch.bfloat16) * 0.05)(C, C) * 0.02),
        "rpb": _w((lambda *s: torch.randn(*s, dtype=torch.bfloat16) * 0.2)((2 * ws - 1) * (2 * ws - 1), nh)),
        "rp_idx": _w(rp_idx),
        "attn_mask": _w(attn_mask),
    }

def reference(x, wqkv, wo, rpb, rp_idx, attn_mask):
    B, H, W, C = x.shape
    N = rp_idx.shape[0]
    ws = int(round(N ** 0.5))
    nh = rpb.shape[-1]
    hd = C // nh
    shift = ws // 2
    xs = torch.roll(x, (-shift, -shift), (1, 2))
    nWh = H // ws
    nWw = W // ws
    xw = (lambda x, *d: x.permute(*d))(xs.reshape(B, nWh, ws, nWw, ws, C), 0, 1, 3, 2, 4, 5).reshape(B * nWh * nWw, N, C)
    qkv = (lambda x, *d: x.permute(*d))(torch.einsum('wnc,cd->wnd', xw, wqkv).reshape(-1, N, 3, nh, hd), 2, 0, 3, 1, 4)
    q, k, v = qkv[0], qkv[1], qkv[2]
    attn = torch.einsum('whid,whjd->whij', q, k) * (hd ** -0.5)
    bias = (lambda x, *d: x.permute(*d))(rpb[rp_idx.reshape(-1)].reshape(N, N, nh), 2, 0, 1)
    attn = attn + bias[None, :, :, :]
    attn = (attn.reshape(B, nWh * nWw, nh, N, N) + attn_mask[None, :, None, :, :]).reshape(-1, nh, N, N)
    attn = _softmax(attn, axis=-1)
    out = (lambda x, *d: x.permute(*d))(torch.einsum('whij,whjd->whid', attn, v), 0, 2, 1, 3).reshape(-1, N, C)
    out = torch.einsum('wnc,cd->wnd', out, wo)
    out = (lambda x, *d: x.permute(*d))(out.reshape(B, nWh, nWw, ws, ws, C), 0, 1, 3, 2, 4, 5).reshape(B, H, W, C)
    return torch.roll(out, (shift, shift), (1, 2))
```

```cpp
#include <cuda_runtime.h>
#include <cuda_bf16.h>
#include <cuda.h>
#include <stdint.h>

namespace {

constexpr int IMG = 512, CH = 192, NWIN = 4096;
constexpr int THREADS = 256;

constexpr uint32_t OFF_X = 0;
constexpr uint32_t OFF_K = 24576;
constexpr uint32_t UB = 1536;
constexpr uint32_t OFF_V = OFF_K + 12288;
constexpr uint32_t OFF_L = OFF_V + 13 * 1024;
constexpr uint32_t OFF_W = OFF_L + 2 * 12288;
constexpr uint32_t W_HALF = 3 * 96 * 64, W_PART = 2 * W_HALF;
constexpr uint32_t WK = OFF_W, WQ = OFF_W + W_PART, WV = OFF_W + 2 * W_PART, WO = OFF_W + 3 * W_PART;
constexpr uint32_t OFF_BAR = OFF_W + 4 * W_PART;
constexpr uint32_t B_XFULL = 0;
constexpr uint32_t B_TOKEN = 32;
constexpr uint32_t B_KFREE = 40, B_VFREE = 48;
constexpr uint32_t B_EX0 = 56, B_EX1 = 64;
constexpr uint32_t B_LFREE = 72;
constexpr uint32_t B_W = OFF_BAR + 256;
constexpr uint32_t B_IDX = OFF_BAR + 296;
constexpr uint32_t B_DONE = OFF_BAR + 304;
constexpr uint32_t OFF_DUMMY = OFF_BAR + 320;
constexpr uint32_t OFF_FAIL = OFF_BAR + 384;
constexpr uint32_t OFF_TAB = OFF_FAIL + 2048;
constexpr uint32_t OFF_TS = OFF_TAB + 1024;
constexpr uint32_t SMEM_BYTES = OFF_TS;

constexpr float LOG2E = 1.4426950408889634f;
constexpr float SCALE = 0.14433756729740643f;

__device__ __forceinline__ uint32_t smem_u32(const void* p) { return (uint32_t)__cvta_generic_to_shared(p); }
__device__ __forceinline__ void wg_fence() { asm volatile("wgmma.fence.sync.aligned;" ::: "memory"); }
__device__ __forceinline__ void wg_commit() { asm volatile("wgmma.commit_group.sync.aligned;" ::: "memory"); }
template <int N> __device__ __forceinline__ void wg_wait() { asm volatile("wgmma.wait_group.sync.aligned %0;" ::"n"(N) : "memory"); }
template <int N> __device__ __forceinline__ void fence_regs(float (&d)[N]) {
#pragma unroll
  for (int i = 0; i < N; i++) asm volatile("" : "+f"(d[i])::"memory");
}
template <int N> __device__ __forceinline__ void fence_regs(uint32_t (&d)[N]) {
#pragma unroll
  for (int i = 0; i < N; i++) asm volatile("" : "+r"(d[i])::"memory");
}
__device__ __forceinline__ bool elect_one() {
  uint32_t pred;
  asm volatile("{\n.reg .pred p;\nelect.sync _|p, 0xffffffff;\nselp.u32 %0, 1, 0, p;\n}\n" : "=r"(pred));
  return pred != 0;
}
__device__ __forceinline__ uint32_t pack_bf16(float lo, float hi) {
  uint32_t r;
  asm("cvt.rn.bf16x2.f32 %0, %1, %2;" : "=r"(r) : "f"(hi), "f"(lo));
  return r;
}
__device__ __forceinline__ float bf_lo(uint32_t v) { return __uint_as_float(v << 16); }
__device__ __forceinline__ float bf_hi(uint32_t v) { return __uint_as_float(v & 0xffff0000u); }
__device__ __forceinline__ float ex2(float x) {
  float y;
  asm("ex2.approx.ftz.f32 %0, %1;" : "=f"(y) : "f"(x));
  return y;
}
__device__ __forceinline__ uint32_t hmul2(uint32_t a, uint32_t b) {
  uint32_t r;
  asm("mul.rn.bf16x2 %0, %1, %2;" : "=r"(r) : "r"(a), "r"(b));
  return r;
}
__device__ __forceinline__ uint32_t dup_lo(uint32_t a) {
  uint32_t r;
  asm("{\n.reg .b16 l, h;\nmov.b32 {l, h}, %1;\nmov.b32 %0, {l, l};\n}\n" : "=r"(r) : "r"(a));
  return r;
}
__device__ __forceinline__ uint32_t dup_hi(uint32_t a) {
  uint32_t r;
  asm("{\n.reg .b16 l, h;\nmov.b32 {l, h}, %1;\nmov.b32 %0, {h, h};\n}\n" : "=r"(r) : "r"(a));
  return r;
}
__device__ __forceinline__ float rcp_approx(float x) {
  float y;
  asm("rcp.approx.ftz.f32 %0, %1;" : "=f"(y) : "f"(x));
  return y;
}
__device__ __forceinline__ uint4 ldg128(const void* p) {
  uint4 v;
  asm volatile("ld.global.L1::evict_normal.v4.u32 {%0,%1,%2,%3}, [%4];" : "=r"(v.x), "=r"(v.y), "=r"(v.z), "=r"(v.w) : "l"(p) : "memory");
  return v;
}
__device__ __forceinline__ void prefetch_l2(const void* p, uint32_t bytes) {
  asm volatile("cp.async.bulk.prefetch.L2.global [%0], %1;" ::"l"(p), "r"(bytes) : "memory");
}
__device__ __forceinline__ uint4 lds128(uint32_t addr) {
  uint4 v;
  asm volatile("ld.shared.v4.u32 {%0,%1,%2,%3}, [%4];" : "=r"(v.x), "=r"(v.y), "=r"(v.z), "=r"(v.w) : "r"(addr) : "memory");
  return v;
}
__device__ __forceinline__ uint4 lds128v(uint32_t addr) {
  uint4 v;
  asm volatile("ld.volatile.shared.v4.u32 {%0,%1,%2,%3}, [%4];" : "=r"(v.x), "=r"(v.y), "=r"(v.z), "=r"(v.w) : "r"(addr) : "memory");
  return v;
}
__device__ __forceinline__ uint32_t lds32(uint32_t addr) {
  uint32_t v;
  asm volatile("ld.shared.u32 %0, [%1];" : "=r"(v) : "r"(addr) : "memory");
  return v;
}
__device__ __forceinline__ void stmatrix_x4(uint32_t addr, uint32_t a, uint32_t b, uint32_t c, uint32_t d) {
  asm volatile("stmatrix.sync.aligned.m8n8.x4.shared.b16 [%0], {%1,%2,%3,%4};" ::"r"(addr), "r"(a), "r"(b), "r"(c), "r"(d) : "memory");
}
__device__ __forceinline__ void ldmatrix_x4(uint32_t addr, uint32_t& a, uint32_t& b, uint32_t& c, uint32_t& d) {
  asm volatile("ldmatrix.sync.aligned.m8n8.x4.shared.b16 {%0,%1,%2,%3}, [%4];" : "=r"(a), "=r"(b), "=r"(c), "=r"(d) : "r"(addr) : "memory");
}
__device__ __forceinline__ void fence_async_proxy() {
  asm volatile("fence.proxy.async.shared::cta;" ::: "memory");
}
__device__ __forceinline__ void wg_barrier(int j) {
  if (j == 0) asm volatile("bar.sync 1, 128;" ::: "memory");
  else asm volatile("bar.sync 2, 128;" ::: "memory");
}
__device__ __forceinline__ void cluster_wait() { asm volatile("barrier.cluster.wait.acquire.aligned;" ::: "memory"); }
__device__ __forceinline__ uint32_t mapa(uint32_t a, uint32_t rank) {
  uint32_t o;
  asm("mapa.shared::cluster.u32 %0, %1, %2;" : "=r"(o) : "r"(a), "r"(rank));
  return o;
}
__device__ __forceinline__ void mbar_init(uint32_t a, uint32_t cnt) { asm volatile("mbarrier.init.shared::cta.b64 [%0], %1;" ::"r"(a), "r"(cnt) : "memory"); }
__device__ __forceinline__ void mbar_expect_tx(uint32_t a, uint32_t tx) {
  asm volatile("mbarrier.arrive.expect_tx.shared::cta.b64 _, [%0], %1;" ::"r"(a), "r"(tx) : "memory");
}
__device__ __forceinline__ void mbar_arrive(uint32_t a) { asm volatile("mbarrier.arrive.shared::cta.b64 _, [%0];" ::"r"(a) : "memory"); }
__device__ __forceinline__ void mbar_arrive4(uint32_t a) { asm volatile("mbarrier.arrive.shared::cta.b64 _, [%0], 4;" ::"r"(a) : "memory"); }
__device__ __forceinline__ uint32_t uniform(uint32_t v) { return __shfl_sync(0xffffffffu, v, 0); }
__device__ __forceinline__ void mbar_arrive_remote_relaxed(uint32_t a) {
  asm volatile("mbarrier.arrive.relaxed.cluster.shared::cluster.b64 _, [%0];" ::"r"(a) : "memory");
}
__device__ __forceinline__ void mbar_wait(uint32_t a, uint32_t parity) {
  asm volatile(
      "{\n.reg .pred p;\n"
      "WAIT_LOOP:\n"
      "mbarrier.try_wait.parity.shared::cta.b64 p, [%0], %1;\n"
      ""
      "@p bra WAIT_DONE;\n"
      "bra WAIT_LOOP;\n"
      "WAIT_DONE:\n}\n" ::"r"(a), "r"(parity) : "memory");
}
__device__ __forceinline__ bool mbar_test(uint32_t a, uint32_t parity) {
  uint32_t ok;
  asm volatile("{\n.reg .pred p;\nmbarrier.test_wait.parity.shared::cta.b64 p, [%1], %2;\nselp.u32 %0, 1, 0, p;\n}\n" : "=r"(ok) : "r"(a), "r"(parity) : "memory");
  return ok != 0;
}
__device__ __forceinline__ uint32_t hfma2(uint32_t a, uint32_t b, uint32_t c) {
  uint32_t r;
  asm("fma.rn.bf16x2 %0, %1, %2, %3;" : "=r"(r) : "r"(a), "r"(b), "r"(c));
  return r;
}
__device__ __forceinline__ void st_async16(uint32_t raddr, uint32_t a, uint32_t b, uint32_t c, uint32_t d, uint32_t rbar) {
  asm volatile("st.async.weak.shared::cluster.mbarrier::complete_tx::bytes.v4.b32 [%0], {%1,%2,%3,%4}, [%5];" ::"r"(raddr),
               "r"(a), "r"(b), "r"(c), "r"(d), "r"(rbar) : "memory");
}

__device__ __forceinline__ void sts128(uint32_t addr, uint4 v) {
  asm volatile("st.shared.v4.u32 [%0], {%1,%2,%3,%4};" ::"r"(addr), "r"(v.x), "r"(v.y), "r"(v.z), "r"(v.w) : "memory");
}
__device__ __forceinline__ void bulk_load(uint32_t dst, const void* src, uint32_t bytes, uint32_t bar) {
  asm volatile("cp.async.bulk.shared::cta.global.mbarrier::complete_tx::bytes [%0], [%1], %2, [%3];" ::"r"(dst), "l"(src),
               "r"(bytes), "r"(bar) : "memory");
}
__device__ __forceinline__ void tma_load3(uint32_t dst, const CUtensorMap* tm, int c1, int c2, uint32_t bar) {
  asm volatile("cp.async.bulk.tensor.3d.shared::cta.global.tile.mbarrier::complete_tx::bytes [%0], [%1, {0, %2, %3}], [%4];" ::"r"(dst),
               "l"(tm), "r"(c1), "r"(c2), "r"(bar) : "memory");
}
__device__ __forceinline__ void tma_load5(uint32_t dst, const CUtensorMap* tm, int c2, int c3, uint32_t bar) {
  asm volatile("cp.async.bulk.tensor.5d.shared::cta.global.tile.mbarrier::complete_tx::bytes [%0], [%1, {0, 0, %2, %3, 0}], [%4];" ::"r"(dst),
               "l"(tm), "r"(c2), "r"(c3), "r"(bar) : "memory");
}
__device__ __forceinline__ void tma_prefetch5(const CUtensorMap* tm, int c2, int c3) {
  asm volatile("cp.async.bulk.prefetch.tensor.5d.L2.global.tile [%0, {0, 0, %1, %2, 0}];" ::"l"(tm), "r"(c2), "r"(c3) : "memory");
}
__device__ __forceinline__ void tma_store5(const CUtensorMap* tm, int c2, int c3, int c4, uint32_t src) {
  asm volatile("cp.async.bulk.tensor.5d.global.shared::cta.tile.bulk_group [%0, {0, 0, %1, %2, %3}], [%4];" ::"l"(tm), "r"(c2), "r"(c3),
               "r"(c4), "r"(src) : "memory");
}
__device__ __forceinline__ void sched_barrier(uint32_t& t, uint32_t zero) {
  asm volatile("{\n.reg .pred p;\nsetp.ne.u32 p, %1, 0;\n@p mov.u32 %0, %%clock;\n}\n" : "+r"(t) : "r"(zero) : "memory");
}

#define TS(i)
#define TS_SET(k)
#define TSS(i)
__device__ __forceinline__ void wgmma_n56_a(float (&d)[28], uint32_t a0, uint32_t a1, uint32_t a2, uint32_t a3, uint64_t db) {
  asm volatile("{\n.reg .pred p;\nsetp.ne.b32 p, 1, 0;\n"
      "wgmma.mma_async.sync.aligned.m64n56k16.f32.bf16.bf16 "
      "{%0,%1,%2,%3,%4,%5,%6,%7,%8,%9,%10,%11,%12,%13,%14,%15,"
      "%16,%17,%18,%19,%20,%21,%22,%23,%24,%25,%26,%27}, "
      "{%28,%29,%30,%31}, %32, p, 1, 1, 1;\n}\n"
      : "+f"(d[0]), "+f"(d[1]), "+f"(d[2]), "+f"(d[3]), "+f"(d[4]), "+f"(d[5]), "+f"(d[6]), "+f"(d[7]),
        "+f"(d[8]), "+f"(d[9]), "+f"(d[10]), "+f"(d[11]), "+f"(d[12]), "+f"(d[13]), "+f"(d[14]), "+f"(d[15]),
        "+f"(d[16]), "+f"(d[17]), "+f"(d[18]), "+f"(d[19]), "+f"(d[20]), "+f"(d[21]), "+f"(d[22]), "+f"(d[23]),
        "+f"(d[24]), "+f"(d[25]), "+f"(d[26]), "+f"(d[27])
      : "r"(a0), "r"(a1), "r"(a2), "r"(a3), "l"(db));
}
__device__ __forceinline__ void wgmma_n56_z(float (&d)[28], uint32_t a0, uint32_t a1, uint32_t a2, uint32_t a3, uint64_t db) {
  asm volatile("{\n.reg .pred p;\nsetp.ne.b32 p, 0, 0;\n"
      "wgmma.mma_async.sync.aligned.m64n56k16.f32.bf16.bf16 "
      "{%0,%1,%2,%3,%4,%5,%6,%7,%8,%9,%10,%11,%12,%13,%14,%15,"
      "%16,%17,%18,%19,%20,%21,%22,%23,%24,%25,%26,%27}, "
      "{%28,%29,%30,%31}, %32, p, 1, 1, 1;\n}\n"
      : "=f"(d[0]), "=f"(d[1]), "=f"(d[2]), "=f"(d[3]), "=f"(d[4]), "=f"(d[5]), "=f"(d[6]), "=f"(d[7]),
        "=f"(d[8]), "=f"(d[9]), "=f"(d[10]), "=f"(d[11]), "=f"(d[12]), "=f"(d[13]), "=f"(d[14]), "=f"(d[15]),
        "=f"(d[16]), "=f"(d[17]), "=f"(d[18]), "=f"(d[19]), "=f"(d[20]), "=f"(d[21]), "=f"(d[22]), "=f"(d[23]),
        "=f"(d[24]), "=f"(d[25]), "=f"(d[26]), "=f"(d[27])
      : "r"(a0), "r"(a1), "r"(a2), "r"(a3), "l"(db));
}
__device__ __forceinline__ void wgmma_n96_a(float (&d)[48], uint32_t a0, uint32_t a1, uint32_t a2, uint32_t a3, uint64_t db) {
  asm volatile("{\n.reg .pred p;\nsetp.ne.b32 p, 1, 0;\n"
      "wgmma.mma_async.sync.aligned.m64n96k16.f32.bf16.bf16 "
      "{%0,%1,%2,%3,%4,%5,%6,%7,%8,%9,%10,%11,%12,%13,%14,%15,"
      "%16,%17,%18,%19,%20,%21,%22,%23,%24,%25,%26,%27,%28,%29,%30,%31,"
      "%32,%33,%34,%35,%36,%37,%38,%39,%40,%41,%42,%43,%44,%45,%46,%47}, "
      "{%48,%49,%50,%51}, %52, p, 1, 1, 1;\n}\n"
      : "+f"(d[0]), "+f"(d[1]), "+f"(d[2]), "+f"(d[3]), "+f"(d[4]), "+f"(d[5]), "+f"(d[6]), "+f"(d[7]),
        "+f"(d[8]), "+f"(d[9]), "+f"(d[10]), "+f"(d[11]), "+f"(d[12]), "+f"(d[13]), "+f"(d[14]), "+f"(d[15]),
        "+f"(d[16]), "+f"(d[17]), "+f"(d[18]), "+f"(d[19]), "+f"(d[20]), "+f"(d[21]), "+f"(d[22]), "+f"(d[23]),
        "+f"(d[24]), "+f"(d[25]), "+f"(d[26]), "+f"(d[27]), "+f"(d[28]), "+f"(d[29]), "+f"(d[30]), "+f"(d[31]),
        "+f"(d[32]), "+f"(d[33]), "+f"(d[34]), "+f"(d[35]), "+f"(d[36]), "+f"(d[37]), "+f"(d[38]), "+f"(d[39]),
        "+f"(d[40]), "+f"(d[41]), "+f"(d[42]), "+f"(d[43]), "+f"(d[44]), "+f"(d[45]), "+f"(d[46]), "+f"(d[47])
      : "r"(a0), "r"(a1), "r"(a2), "r"(a3), "l"(db));
}
__device__ __forceinline__ void wgmma_n96_z(float (&d)[48], uint32_t a0, uint32_t a1, uint32_t a2, uint32_t a3, uint64_t db) {
  asm volatile("{\n.reg .pred p;\nsetp.ne.b32 p, 0, 0;\n"
      "wgmma.mma_async.sync.aligned.m64n96k16.f32.bf16.bf16 "
      "{%0,%1,%2,%3,%4,%5,%6,%7,%8,%9,%10,%11,%12,%13,%14,%15,"
      "%16,%17,%18,%19,%20,%21,%22,%23,%24,%25,%26,%27,%28,%29,%30,%31,"
      "%32,%33,%34,%35,%36,%37,%38,%39,%40,%41,%42,%43,%44,%45,%46,%47}, "
      "{%48,%49,%50,%51}, %52, p, 1, 1, 1;\n}\n"
      : "=f"(d[0]), "=f"(d[1]), "=f"(d[2]), "=f"(d[3]), "=f"(d[4]), "=f"(d[5]), "=f"(d[6]), "=f"(d[7]),
        "=f"(d[8]), "=f"(d[9]), "=f"(d[10]), "=f"(d[11]), "=f"(d[12]), "=f"(d[13]), "=f"(d[14]), "=f"(d[15]),
        "=f"(d[16]), "=f"(d[17]), "=f"(d[18]), "=f"(d[19]), "=f"(d[20]), "=f"(d[21]), "=f"(d[22]), "=f"(d[23]),
        "=f"(d[24]), "=f"(d[25]), "=f"(d[26]), "=f"(d[27]), "=f"(d[28]), "=f"(d[29]), "=f"(d[30]), "=f"(d[31]),
        "=f"(d[32]), "=f"(d[33]), "=f"(d[34]), "=f"(d[35]), "=f"(d[36]), "=f"(d[37]), "=f"(d[38]), "=f"(d[39]),
        "=f"(d[40]), "=f"(d[41]), "=f"(d[42]), "=f"(d[43]), "=f"(d[44]), "=f"(d[45]), "=f"(d[46]), "=f"(d[47])
      : "r"(a0), "r"(a1), "r"(a2), "r"(a3), "l"(db));
}
__device__ __forceinline__ void wgmma_n96_p(float (&d)[48], uint32_t a0, uint32_t a1, uint32_t a2, uint32_t a3, uint64_t db, uint32_t acc) {
  asm volatile("{\n.reg .pred p;\nsetp.ne.b32 p, %53, 0;\n"
      "wgmma.mma_async.sync.aligned.m64n96k16.f32.bf16.bf16 "
      "{%0,%1,%2,%3,%4,%5,%6,%7,%8,%9,%10,%11,%12,%13,%14,%15,"
      "%16,%17,%18,%19,%20,%21,%22,%23,%24,%25,%26,%27,%28,%29,%30,%31,"
      "%32,%33,%34,%35,%36,%37,%38,%39,%40,%41,%42,%43,%44,%45,%46,%47}, "
      "{%48,%49,%50,%51}, %52, p, 1, 1, 1;\n}\n"
      : "+f"(d[0]), "+f"(d[1]), "+f"(d[2]), "+f"(d[3]), "+f"(d[4]), "+f"(d[5]), "+f"(d[6]), "+f"(d[7]),
        "+f"(d[8]), "+f"(d[9]), "+f"(d[10]), "+f"(d[11]), "+f"(d[12]), "+f"(d[13]), "+f"(d[14]), "+f"(d[15]),
        "+f"(d[16]), "+f"(d[17]), "+f"(d[18]), "+f"(d[19]), "+f"(d[20]), "+f"(d[21]), "+f"(d[22]), "+f"(d[23]),
        "+f"(d[24]), "+f"(d[25]), "+f"(d[26]), "+f"(d[27]), "+f"(d[28]), "+f"(d[29]), "+f"(d[30]), "+f"(d[31]),
        "+f"(d[32]), "+f"(d[33]), "+f"(d[34]), "+f"(d[35]), "+f"(d[36]), "+f"(d[37]), "+f"(d[38]), "+f"(d[39]),
        "+f"(d[40]), "+f"(d[41]), "+f"(d[42]), "+f"(d[43]), "+f"(d[44]), "+f"(d[45]), "+f"(d[46]), "+f"(d[47])
      : "r"(a0), "r"(a1), "r"(a2), "r"(a3), "l"(db), "r"(acc));
}
__device__ __forceinline__ void wgmma_n64_a(float (&d)[32], uint32_t a0, uint32_t a1, uint32_t a2, uint32_t a3, uint64_t db) {
  asm volatile("{\n.reg .pred p;\nsetp.ne.b32 p, 1, 0;\n"
      "wgmma.mma_async.sync.aligned.m64n64k16.f32.bf16.bf16 "
      "{%0,%1,%2,%3,%4,%5,%6,%7,%8,%9,%10,%11,%12,%13,%14,%15,"
      "%16,%17,%18,%19,%20,%21,%22,%23,%24,%25,%26,%27,%28,%29,%30,%31}, "
      "{%32,%33,%34,%35}, %36, p, 1, 1, 0;\n}\n"
      : "+f"(d[0]), "+f"(d[1]), "+f"(d[2]), "+f"(d[3]), "+f"(d[4]), "+f"(d[5]), "+f"(d[6]), "+f"(d[7]),
        "+f"(d[8]), "+f"(d[9]), "+f"(d[10]), "+f"(d[11]), "+f"(d[12]), "+f"(d[13]), "+f"(d[14]), "+f"(d[15]),
        "+f"(d[16]), "+f"(d[17]), "+f"(d[18]), "+f"(d[19]), "+f"(d[20]), "+f"(d[21]), "+f"(d[22]), "+f"(d[23]),
        "+f"(d[24]), "+f"(d[25]), "+f"(d[26]), "+f"(d[27]), "+f"(d[28]), "+f"(d[29]), "+f"(d[30]), "+f"(d[31])
      : "r"(a0), "r"(a1), "r"(a2), "r"(a3), "l"(db));
}
__device__ __forceinline__ void wgmma_n64_z(float (&d)[32], uint32_t a0, uint32_t a1, uint32_t a2, uint32_t a3, uint64_t db) {
  asm volatile("{\n.reg .pred p;\nsetp.ne.b32 p, 0, 0;\n"
      "wgmma.mma_async.sync.aligned.m64n64k16.f32.bf16.bf16 "
      "{%0,%1,%2,%3,%4,%5,%6,%7,%8,%9,%10,%11,%12,%13,%14,%15,"
      "%16,%17,%18,%19,%20,%21,%22,%23,%24,%25,%26,%27,%28,%29,%30,%31}, "
      "{%32,%33,%34,%35}, %36, p, 1, 1, 0;\n}\n"
      : "=f"(d[0]), "=f"(d[1]), "=f"(d[2]), "=f"(d[3]), "=f"(d[4]), "=f"(d[5]), "=f"(d[6]), "=f"(d[7]),
        "=f"(d[8]), "=f"(d[9]), "=f"(d[10]), "=f"(d[11]), "=f"(d[12]), "=f"(d[13]), "=f"(d[14]), "=f"(d[15]),
        "=f"(d[16]), "=f"(d[17]), "=f"(d[18]), "=f"(d[19]), "=f"(d[20]), "=f"(d[21]), "=f"(d[22]), "=f"(d[23]),
        "=f"(d[24]), "=f"(d[25]), "=f"(d[26]), "=f"(d[27]), "=f"(d[28]), "=f"(d[29]), "=f"(d[30]), "=f"(d[31])
      : "r"(a0), "r"(a1), "r"(a2), "r"(a3), "l"(db));
}

template <uint32_t OFF, uint32_t LBO>
__device__ __forceinline__ uint64_t desc_at(uint64_t base) {
  return base + (uint64_t)((OFF >> 4) + ((LBO >> 4) << 16));
}
template <uint32_t SBO, uint32_t SWIZZLE = 0>
__device__ __forceinline__ uint64_t desc_base(uint32_t addr4) {
  return ((uint64_t)SWIZZLE << 62) | ((uint64_t)(SBO >> 4) << 32) | (uint64_t)addr4;
}
__device__ __forceinline__ uint64_t pin(uint64_t v) {
  asm volatile("" : "+l"(v));
  return v;
}
template <int I> struct IC { static constexpr int v = I; };
template <int N, class F> __device__ __forceinline__ void static_for(F&& f) {
  if constexpr (N > 0) { static_for<N - 1>(f); f(IC<N - 1>{}); }
}

__device__ __forceinline__ void quad_origin(int win, int w, bool valid, int& row, int& col2) {
  col2 = (4 * (win & 63) + 2 + 2 * (w & 1)) & (IMG / 2 - 1);
  row = (8 * (win >> 6) + 4 + 4 * (w >> 1)) & (IMG - 1);
  if (!valid) row = IMG;
}
__device__ __forceinline__ void load_tile(uint32_t dst, int warp, int win, bool valid, uint32_t xbar, const CUtensorMap* tm_x) {
  int row, col2;
  quad_origin(win, warp, valid, row, col2);
  if (elect_one()) {
    mbar_expect_tx(xbar, 6144);
    tma_load5(dst, tm_x, row, col2, xbar);
  }
}
template <int S>
__device__ __forceinline__ void read_x(uint32_t (&xa)[48], const uint32_t (&xaddr)[4]) {
  ldmatrix_x4(xaddr[S & 3] + (S >> 2) * 2048, xa[4 * S], xa[4 * S + 1], xa[4 * S + 2], xa[4 * S + 3]);
}
__device__ __forceinline__ void reads_done(uint32_t last, uint32_t dummy_addr) {
  asm volatile("{\n.reg .pred p;\nsetp.eq.u32 p, %0, 0x7fc1fc17;\n@p st.shared.u32 [%1], %0;\n}\n" ::"r"(last), "r"(dummy_addr) : "memory");
}
template <int P>
__device__ __forceinline__ void store_chunk(uint32_t addr, float (&d)[48]) {
  stmatrix_x4(addr, pack_bf16(d[8 * P + 0], d[8 * P + 1]), pack_bf16(d[8 * P + 2], d[8 * P + 3]),
              pack_bf16(d[8 * P + 4], d[8 * P + 5]), pack_bf16(d[8 * P + 6], d[8 * P + 7]));
}
template <uint32_t WOFF, int H, bool TIED, class F>
__device__ __forceinline__ void gemm_phase(float (&run)[48], uint32_t (&x)[48], uint64_t w4, uint32_t rzero, F&& after) {
  wg_fence();
  static_for<12>([&](auto I) {
    constexpr int s = decltype(I)::v;
    const uint64_t d = desc_at<WOFF + (s / 6) * W_HALF + (s % 6) * 1024, 6144>(pin(w4));
    if constexpr (s == 0 && TIED) wgmma_n96_p(run, x[0], x[1], x[2], x[3], d, rzero);
    else if constexpr (s == 0) wgmma_n96_z(run, x[0], x[1], x[2], x[3], d);
    else wgmma_n96_a(run, x[4 * s], x[4 * s + 1], x[4 * s + 2], x[4 * s + 3], d);
    if constexpr (s == H - 1 || s == 11) wg_commit();
    if constexpr (s == H - 1) wg_wait<1>();
    after(I);
  });
}
template <int H>
__device__ __forceinline__ void issue_s(float (&s)[32], uint32_t (&q)[24], uint64_t k4_) {
  const uint64_t k4 = pin(k4_);
  static_for<3>([&](auto I) {
    constexpr int k = decltype(I)::v, i = 12 * H + 4 * k;
    const uint64_t d = desc_at<OFF_K + H * 768 + k * 256, 128>(k4);
    if constexpr (k == 0) wgmma_n64_z(s, q[i], q[i + 1], q[i + 2], q[i + 3], d);
    else wgmma_n64_a(s, q[i], q[i + 1], q[i + 2], q[i + 3], d);
  });
  wg_commit();
}
__device__ __forceinline__ const uint8_t* offset_ptr(const uint8_t* base, uint32_t off) {
  const uint8_t* r;
  asm volatile("{\n.reg .u64 o;\ncvt.u64.u32 o, %2;\nadd.u64 %0, %1, o;\n}\n" : "=l"(r) : "l"(base), "r"(off));
  return r;
}
struct MaskRows { uint4 a, b, c, d; };
__device__ __forceinline__ MaskRows mask_load(const uint8_t* mp) {
  MaskRows r;
  r.a = ldg128(mp); r.b = ldg128(mp + 1024); r.c = ldg128(mp + 2048); r.d = ldg128(mp + 3072);
  return r;
}
__device__ __forceinline__ uint32_t mask_or(const MaskRows& r) {
  return (r.a.x | r.a.y | r.a.z | r.a.w) | (r.b.x | r.b.y | r.b.z | r.b.w) | (r.c.x | r.c.y | r.c.z | r.c.w) | (r.d.x | r.d.y | r.d.z | r.d.w);
}
__device__ __forceinline__ void shift_logits(float (&s0)[32], float (&s1)[32], const uint8_t* mp) {
  const uint4 m[4] = {ldg128(mp), ldg128(mp + 64), ldg128(mp + 256), ldg128(mp + 320)};
#pragma unroll
  for (int t = 0; t < 2; t++) {
    float x0 = -INFINITY, x1 = -INFINITY;
#pragma unroll
    for (int b = 0; b < 8; b++) {
      const uint4 u = m[2 * t + (b >> 2)];
      const uint32_t v = (b & 3) == 0 ? u.x : (b & 3) == 1 ? u.y : (b & 3) == 2 ? u.z : u.w;
      const int i = 4 * b + 2 * t;
      s0[i] = fmaf(bf_lo(v), LOG2E, s0[i]); s0[i + 1] = fmaf(bf_hi(v), LOG2E, s0[i + 1]);
      s1[i] = fmaf(bf_lo(v), LOG2E, s1[i]); s1[i + 1] = fmaf(bf_hi(v), LOG2E, s1[i + 1]);
      x0 = fmaxf(x0, fmaxf(s0[i], s0[i + 1]));
      x1 = fmaxf(x1, fmaxf(s1[i], s1[i + 1]));
    }
    x0 = fmaxf(x0, __shfl_xor_sync(0xffffffffu, x0, 1)); x1 = fmaxf(x1, __shfl_xor_sync(0xffffffffu, x1, 1));
    x0 = fmaxf(x0, __shfl_xor_sync(0xffffffffu, x0, 2)); x1 = fmaxf(x1, __shfl_xor_sync(0xffffffffu, x1, 2));
#pragma unroll
    for (int b = 0; b < 8; b++) {
      const int i = 4 * b + 2 * t;
      s0[i] -= x0; s0[i + 1] -= x0;
      s1[i] -= x1; s1[i + 1] -= x1;
    }
  }
}
template <int I0, int I1>
__device__ __forceinline__ void exponentiate(float (&s)[32], const uint32_t (&eb)[16], uint32_t (&p)[16]) {
#pragma unroll
  for (int i = I0; i < I1; i++) {
    asm volatile("" : "+f"(s[2 * i]), "+f"(s[2 * i + 1])::"memory");
    p[i] = hmul2(pack_bf16(ex2(s[2 * i]), ex2(s[2 * i + 1])), eb[i]);
    asm volatile("" : "+r"(p[i])::"memory");
  }
}
template <int H>
__device__ __forceinline__ void issue_pv(float (&oacc)[28], uint32_t (&p)[16], uint64_t v4_) {
  const uint64_t v4 = pin(v4_);
  static_for<4>([&](auto I) {
    constexpr int k = decltype(I)::v;
    const uint64_t d = desc_at<OFF_V + H * 6144 + k * 256, 128>(v4);
    if constexpr (k == 0) wgmma_n56_z(oacc, p[0], p[1], p[2], p[3], d);
    else wgmma_n56_a(oacc, p[4 * k], p[4 * k + 1], p[4 * k + 2], p[4 * k + 3], d);
  });
  wg_commit();
}
constexpr uint32_t BAD_SUM = 0xE000E000u;
template <int H>
__device__ __forceinline__ uint32_t normalize(float (&oacc)[28], uint32_t (&o)[48]) {
  const float r0 = rcp_approx(oacc[H ? 0 : 24]), r1 = rcp_approx(oacc[H ? 2 : 26]);
  const uint32_t r = pack_bf16(r0, r1), ra = dup_lo(r), rb = dup_hi(r);
#pragma unroll
  for (int k = 0; k < 12; k++) o[12 * H + k] = hmul2(pack_bf16(oacc[4 * H + 2 * k], oacc[4 * H + 2 * k + 1]), (k & 1) ? rb : ra);
  return r - 0x2F802F80u;
}

struct Params {
  const __nv_bfloat16 *x, *wqkv, *wo, *rpb;
  const int* rp_idx;
  const __nv_bfloat16* mask;
  __nv_bfloat16* out;
  int nclusters, nk_min, nk_rem;
};
__device__ __forceinline__ float round_bf16(float v) { return __bfloat162float(__float2bfloat16(v)); }
__device__ __forceinline__ void redo_window(const Params& P, float* sm, int win, int rank) {
  float* xt = sm;
  float* qkv = sm + 192 * 64;
  const int tid = threadIdx.x;
  auto pixel = [&](int n) { return (size_t)(((8 * (win >> 6) + (n >> 3) + 4) & (IMG - 1)) * IMG + ((8 * (win & 63) + (n & 7) + 4) & (IMG - 1))) * CH; };
  auto gemm = [&](const __nv_bfloat16* w, int ldw, int ncols, auto&& put) {
    for (int e = tid; e < 4 * ncols; e += THREADS) {
      const int g = e / ncols, d = e - g * ncols;
      float acc[16];
#pragma unroll
      for (int i = 0; i < 16; i++) acc[i] = 0.f;
      for (int c = 0; c < CH; c++) {
        const float wv = __bfloat162float(w[c * ldw + d]);
#pragma unroll
        for (int i = 0; i < 16; i++) acc[i] = fmaf(xt[c * 64 + 16 * g + i], wv, acc[i]);
      }
#pragma unroll
      for (int i = 0; i < 16; i++) put(16 * g + i, d, acc[i]);
    }
  };
  __syncthreads();
  for (int e = tid; e < 64 * CH; e += THREADS) xt[(e % CH) * 64 + e / CH] = __bfloat162float(P.x[pixel(e / CH) + e % CH]);
  __syncthreads();
  gemm(P.wqkv, 3 * CH, 3 * CH, [&](int n, int d, float v) { qkv[n * 577 + d] = round_bf16(v); });
  __syncthreads();
  {
    const int n = tid & 63, h = tid >> 6;
    auto logit = [&](int m) {
      float s = 0.f;
      for (int d = 0; d < 48; d++) s = fmaf(qkv[n * 577 + 48 * h + d], qkv[m * 577 + CH + 48 * h + d], s);
      return s * SCALE + __bfloat162float(P.rpb[P.rp_idx[n * 64 + m] * 4 + h]) + __bfloat162float(P.mask[(size_t)win * 4096 + n * 64 + m]);
    };
    float mx = -INFINITY, sum = 0.f, o[48];
    for (int m = 0; m < 64; m++) mx = fmaxf(mx, logit(m));
#pragma unroll
    for (int d = 0; d < 48; d++) o[d] = 0.f;
    for (int m = 0; m < 64; m++) {
      const float p = expf(logit(m) - mx);
      sum += p;
#pragma unroll
      for (int d = 0; d < 48; d++) o[d] = fmaf(p, qkv[m * 577 + 2 * CH + 48 * h + d], o[d]);
    }
#pragma unroll
    for (int d = 0; d < 48; d++) xt[(48 * h + d) * 64 + n] = round_bf16(o[d] / sum);
  }
  __syncthreads();
  gemm(P.wo + 96 * rank, CH, 96, [&](int n, int d, float v) { P.out[pixel(n) + 96 * rank + d] = __float2bfloat16(v); });
}

#define HD 6
#define HO HD
#define HQ HD
#define HV HD
#define E0 5
#define E1 10
#define ET 3
#define TOK 13
#define XSL "11110022220000"
#define XD 11
#define MS 8
#define PFP 12
#define KF 2
#define LF 7
#define SCHV force
#define QT 0
#define MSB 1
#define WPF 1
#define TPF 1
#define KW 0
#define X1P 1
#define OF (E1 >= 12 ? 8 : -1)
#define OF2 (E0 >= 12 ? 5 : -1)
#define M1E 0
#define SBM 0
#define TSB(i) do { if ((SBM >> (i)) & 1) sched(); TS(i); } while (0)
#define GE 1
#define NB 2
__host__ __device__ constexpr int xslot(int i) { return XSL[i] - '0'; }
__host__ __device__ constexpr int xbase(int i) { int b = 0; for (int q = 0; q < i; q++) b += xslot(q); return b; }
__host__ __device__ constexpr int xlast() { int l = 0; for (int q = 0; q < 14; q++) if (xslot(q)) l = q; return l; }
static_assert(xbase(14) == 12 && XD >= xlast(), "X schedule");

__global__ void __cluster_dims__(2, 1, 1) __launch_bounds__(THREADS, 1)
swin_attn_kernel(const __grid_constant__ CUtensorMap tm_x, const __grid_constant__ CUtensorMap tm_o, const __grid_constant__ CUtensorMap tm_w,
                 const __grid_constant__ CUtensorMap tm_wo, const __grid_constant__ Params P) {
  extern __shared__ __align__(1024) uint8_t smem_raw[];
  const uint32_t sbase = __shfl_sync(0xffffffffu, smem_u32(smem_raw), 0);
  if (sbase & 1023) __trap();
  const int tid = threadIdx.x;
  const int j = uniform(tid >> 7);
  const int warp = uniform((tid >> 5) & 3);
  const uint32_t lane = tid & 31;
  uint32_t rank;
  asm("mov.u32 %0, %%cluster_ctarank;" : "=r"(rank));
  const int cluster = blockIdx.x >> 1;
  const int nk = uniform(P.nk_min + (cluster < P.nk_rem));
  const bool special = P.nclusters == 66;
  const int wbase = uniform(!special ? cluster : cluster < 4 ? 63 * cluster : 10 + 60 * cluster);
  const int wstride = uniform(special ? 1 : P.nclusters), wskip = uniform(special ? 16645 : 0);
  auto window = [&](int k) { const int a = wbase + k * wstride; return a + (int)((uint32_t)(a * wskip) >> 20); };
  auto window_any = [&](int k) {
    const int v = 2 * (cluster - 4) + k;
    return (k >= 2 || !special || cluster < 4) ? window(k) : v < 61 ? 4035 + v : 64 * (v - 61) + 63;
  };
  int win = uniform(window_any(j));
  const uint32_t bar = uniform(smem_u32(smem_raw) + OFF_BAR + (tid & 128)), bar_o = uniform(smem_u32(smem_raw) + OFF_BAR + ((tid & 128) ^ 128));
  const uint32_t xbar = uniform(smem_u32(smem_raw) + OFF_BAR + (tid & 128) + B_XFULL + 8 * ((tid >> 5) & 3));
  const uint32_t xbar_o = uniform(smem_u32(smem_raw) + OFF_BAR + ((tid & 128) ^ 128) + B_XFULL + 8 * ((tid >> 5) & 3));
  const uint32_t xdst = uniform(smem_u32(smem_raw) + OFF_X + ((tid >> 5) & 3) * 6144);
  const uint8_t* mask_b = reinterpret_cast<const uint8_t*>(P.mask);
  const uint32_t quad_row = 32 * (warp >> 1) + 4 * (warp & 1);
  const uint8_t* mask_q = mask_b + quad_row * 128;
  auto load_w = [&](int part) {
#pragma unroll
    for (int h = 0; h < 2; h++) {
      const uint32_t b = sbase + B_W + (part == 0 && h == 0 ? 32 : 8 * part);
      if (part == 0 || h == 0) mbar_expect_tx(b, part == 0 ? W_HALF : W_PART);
      if (part < 3) tma_load3(sbase + OFF_W + part * W_PART + h * W_HALF, &tm_w, 96 * h, (part == 0 ? 6 : part == 1 ? 0 : 12) + 3 * rank, b);
      else tma_load3(sbase + WO + h * W_HALF, &tm_wo, 96 * (rank ^ h), 3 * rank, b);
    }
  };
  uint32_t tab[2] = {0, 0};
  if (j == 1) {
    const uint32_t* tp = reinterpret_cast<const uint32_t*>(P.rpb) + 2 * tid + rank;
    asm volatile("ld.global.nc.u32 %0, [%1];" : "=r"(tab[0]) : "l"(tp - 256) : "memory");
    if (tid < 225) asm volatile("ld.global.nc.u32 %0, [%1];" : "=r"(tab[1]) : "l"(tp) : "memory");
  }
  if (elect_one()) {
    if (WPF && j == 1 && warp == 2 && blockIdx.x < 128)
      prefetch_l2(blockIdx.x < 96 ? reinterpret_cast<const uint8_t*>(P.wqkv) + blockIdx.x * 2304 : reinterpret_cast<const uint8_t*>(P.wo) + (blockIdx.x - 96) * 2304, 2304);
    if (TPF && j == 1 && warp == 3) asm volatile("prefetch.tensormap [%0];" ::"l"(&tm_w) : "memory");
    mbar_init(xbar, 1);
    if (j == KW) {
      mbar_init(sbase + B_W + 8 * warp, 1);
      if (warp < 2) mbar_init(sbase + B_W + 32 + 8 * warp, 1);
    }
    asm volatile("fence.mbarrier_init.release.cluster;" ::: "memory");
  }
  __syncwarp();
  if (j == 0) load_tile(xdst, warp, win, true, xbar, &tm_x);
  if (j == KW && warp < 2 && elect_one()) {
    if (warp == 0) load_w(0);
    else {
      mbar_expect_tx(sbase + B_IDX, 16384);
      bulk_load(sbase + WO, P.rp_idx, 16384, sbase + B_IDX);
    }
  }
  TS(24);
  MaskRows mr;
  if (j == 0 || M1E) mr = mask_load(mask_q + (size_t)win * 8192 + lane * 16);
  asm volatile("st.shared.u32 [%0], %1;" ::"r"(sbase + OFF_FAIL + 4 * tid), "r"(0) : "memory");
  if (warp == 1) {
    if (elect_one()) {
      mbar_init(bar + B_TOKEN, 4);
      mbar_init(bar + B_KFREE, 4);
      mbar_init(bar + B_VFREE, 4);
      if (j == 0) {
        mbar_arrive4(bar + B_TOKEN);
        mbar_arrive4(bar + B_VFREE);
      }
    }
  } else if (warp == 2) {
    if (elect_one()) {
      mbar_init(bar + B_EX0, 4);
      mbar_init(bar + B_EX1, 4);
      mbar_init(bar + B_LFREE, 4);
      if (j) mbar_init(sbase + B_DONE, 8);
      asm volatile("fence.mbarrier_init.release.cluster;" ::: "memory");
    }
  } else if (warp == 3) {
    sts128(sbase + OFF_V + 6144 + j * 512 + lane * 16, make_uint4(0x3F803F80u, 0x3F803F80u, 0x3F803F80u, 0x3F803F80u));
  }
  TS(25);
  __syncthreads();
  asm volatile("barrier.cluster.arrive.relaxed.aligned;" ::: "memory");
  TS(26);
  if (j == 1) {
    if (X1P == 0) load_tile(xdst + OFF_L, warp, win, true, xbar, &tm_x);
    if (warp == 1 && elect_one()) load_w(1);
  }
  TS(27);
  const uint32_t sb_a = uniform((sbase & 0x3FFFF) >> 4);
  const uint64_t w4 = desc_base<512, 2>(sb_a), k4 = desc_base<UB>(sb_a), v4 = desc_base<1024>(sb_a);
  const uint32_t blk = 2 * warp + ((lane >> 3) & 1);
  uint32_t stk = sbase + OFF_K + blk * UB + (lane >> 4) * 128 + (lane & 7) * 16;
  uint32_t stv = sbase + OFF_V + (lane >> 4) * 1024 + blk * 128 + (lane & 7) * 16;
  uint32_t xaddr0 = xdst + (lane & 15) * 128 + (((lane >> 4) ^ (lane & 7)) << 4);
  const uint32_t peer = rank ^ 1;
  const uint32_t area = uniform(smem_u32(smem_raw) + OFF_L + (tid >> 5) * 3072);
  const uint32_t r_bar = uniform(mapa(bar, peer)), r_area = uniform(mapa(area, peer));
  uint32_t l16 = lane * 16;
  uint32_t out_res = area + (lane & 15) * 64 + (((lane >> 4) ^ ((lane >> 1) & 3)) << 4);
  const uint32_t rzero = uniform((uint32_t)P.nclusters >> 20);

  sched_barrier(stk, rzero); sched_barrier(stv, rzero); sched_barrier(xaddr0, rzero); sched_barrier(out_res, rzero); sched_barrier(l16, rzero);
  uint32_t xa[48], oo[48], eb0[16], eb1[16];
  auto fetch = [&](auto H) {
    constexpr int o = 24 + 12 * decltype(H)::v;
    const uint32_t addr = area + l16 + 1536 * decltype(H)::v;
    const uint4 x = lds128v(addr), y = lds128v(addr + 512), z = lds128v(addr + 1024);
    oo[o + 0] = x.x; oo[o + 1] = x.y; oo[o + 2] = x.z; oo[o + 3] = x.w; oo[o + 4] = y.x; oo[o + 5] = y.y; oo[o + 6] = y.z; oo[o + 7] = y.w;
    oo[o + 8] = z.x; oo[o + 9] = z.y; oo[o + 10] = z.z; oo[o + 11] = z.w;
  };
  auto store_out = [&](auto PP, float (&d)[48]) {
    constexpr int p = decltype(PP)::v;
    store_chunk<p>(((p & 1) ? (out_res ^ 32) : out_res) + (p >> 1) * 1024, d);
  };
  auto send_out = [&](int w, bool valid) {
    int row, col2;
    quad_origin(w, warp, valid, row, col2);
    if (elect_one()) tma_store5(&tm_o, row, col2, 3 * rank, area);
    asm volatile("cp.async.bulk.commit_group;" ::: "memory");
  };
  auto prefetch_mask = [&](int w) {
    if (elect_one()) prefetch_l2(mask_b + (size_t)w * 8192 + (rank * 4 + warp) * 1024, 1024);
  };
  auto prefetch_x = [&](int w) {
    if ((warp >> 1) == rank) {
      int row, col2;
      quad_origin(w, warp, true, row, col2);
      if (elect_one()) tma_prefetch5(&tm_x, row, col2);
    }
  };

  auto first_x = [&]() {
    uint32_t xaddr[4], all = ~0u;
#pragma unroll
    for (int q = 0; q < 4; q++) xaddr[q] = (xaddr0 + j * OFF_L) ^ (q << 5);
    mbar_wait(xbar, 0);
    TS(29);
    static_for<12>([&](auto I) { read_x<decltype(I)::v>(xa, xaddr); all &= xa[4 * decltype(I)::v + 3]; });
    reads_done(all, sbase + OFF_DUMMY);
    TS(30);
  };
  auto gather = [&]() {
    const uint32_t odd = (lane >> 2) & 1;
    const uint32_t ia = sbase + WO + (quad_row + 8 * (lane >> 3) + odd) * 256 + (lane & 3) * 32;
    mbar_wait(sbase + B_IDX, 0);
#pragma unroll
    for (int i = 0; i < 4; i++) {
      const int t = i >> 1, b = 4 * (i & 1);
      const uint4 u0 = lds128(ia + t * 512 + (i & 1) * 128 + odd * 16), u1 = lds128(ia + t * 512 + (i & 1) * 128 + 16 - odd * 16);
      const uint32_t id[8] = {u0.x, u0.y, u0.z, u0.w, u1.x, u1.y, u1.z, u1.w};
      uint32_t v[8];
#pragma unroll
      for (int q = 0; q < 8; q++) v[q] = lds32(sbase + OFF_TAB + 4 * id[q]);
#pragma unroll
      for (int q = 0; q < 4; q++) {
        const uint32_t x = odd ? v[(2 * q) ^ 4] : v[2 * q], y = odd ? v[(2 * q + 1) ^ 4] : v[2 * q + 1];
        eb0[2 * (b + q) + t] = __byte_perm(x, y, 0x5410);
        eb1[2 * (b + q) + t] = __byte_perm(x, y, 0x7632);
      }
    }
    TS(31);
  };
  if (j == 0) first_x();
  bool big = false;
  if (j == 1) {
#pragma unroll
    for (int i = 0; i < 2; i++) {
      const float b0 = bf_lo(tab[i]) * LOG2E, b1 = bf_hi(tab[i]) * LOG2E;
      asm volatile("st.shared.u32 [%0], %1;" ::"r"(sbase + OFF_TAB + 4 * (tid - 128) + 512 * i), "r"(pack_bf16(ex2(b0), ex2(b1))) : "memory");
      big = big || !(fabsf(b0) <= 60.f && fabsf(b1) <= 60.f);
    }
  }
  TS(28);
  if (j == 1) {
    if (X1P == 1) load_tile(xdst + OFF_L, warp, win, true, xbar, &tm_x);
    if (warp == 2 && elect_one()) load_w(2);
    if (X1P == 2) load_tile(xdst + OFF_L, warp, win, true, xbar, &tm_x);
  }
  uint32_t force = 0;
  if (GE) {
    force = __syncthreads_or(big) ? BAD_SUM : 0u;
    if (j == 0) gather();
  }
#pragma unroll
  for (int h = 0; h < 2; h++) {
    constexpr uint32_t HI = 0x3E553E55u, LO = 0x396E396Eu;
    const uint32_t a = sbase + WK + h * 16384 + tid * 16;
    uint4 v[5];
    if (h == 0) mbar_wait(sbase + B_W + 32, 0);
    else mbar_wait(sbase + B_W, 0);
    TS(32 + h);
#pragma unroll
    for (int i = 0; i < 4 + h; i++) v[i] = lds128(a + i * 4096);
#pragma unroll
    for (int i = 0; i < 4 + h; i++)
      sts128(a + i * 4096, make_uint4(hfma2(v[i].x, HI, hmul2(v[i].x, LO)), hfma2(v[i].y, HI, hmul2(v[i].y, LO)),
                                      hfma2(v[i].z, HI, hmul2(v[i].z, LO)), hfma2(v[i].w, HI, hmul2(v[i].w, LO))));
  }
  fence_async_proxy();
  TS(21);
  if (GE) __syncthreads();
  else force = __syncthreads_or(big) ? BAD_SUM : 0u;
  TS(22);
  if (j == 1) {
    if (!M1E) mr = mask_load(mask_q + (size_t)win * 8192 + lane * 16);
    first_x();
    __syncwarp();
    if (lane == 0) mbar_arrive(bar_o + B_KFREE);
    load_tile(xdst, warp, window(2), 2 < nk, xbar_o, &tm_x);
  }
  if (!GE || j == 1) gather();
#pragma unroll
  for (int i = 0; i < 16; i += 4) {
    asm volatile("{\n.reg .pred p;\nsetp.ne.u32 p, %4, 0;\n@p ld.shared.v4.u32 {%0,%1,%2,%3}, [%4];\n}\n" : "+r"(eb0[i]), "+r"(eb0[i + 1]), "+r"(eb0[i + 2]), "+r"(eb0[i + 3]) : "r"(rzero));
    asm volatile("{\n.reg .pred p;\nsetp.ne.u32 p, %4, 0;\n@p ld.shared.v4.u32 {%0,%1,%2,%3}, [%4];\n}\n" : "+r"(eb1[i]), "+r"(eb1[i + 1]), "+r"(eb1[i + 2]), "+r"(eb1[i + 3]) : "r"(rzero));
  }
  if (j == 1) {
    if (3 < nk) prefetch_x(window(3));
    if (2 < nk) prefetch_mask(window(2));
    if (3 < nk) prefetch_mask(window(3));
  }
  bool shifted = __any_sync(0xffffffffu, (mask_or(mr) | force) != 0);

  uint32_t par = 0;
  auto sched = [&]() { sched_barrier(SCHV, rzero); };
  int k = j, wprev = win;
#pragma unroll
  for (int i = 0; i < 48; i++) oo[i] = 0;
  TS(23);
  for (;;) {
    float ca[48], cb[48], s0[32], s1[32];
    uint32_t qf[24];
    bool ex0, ex1, kfree;
    TSB(1);
    fence_regs(xa);
    auto ex_step = [&](auto G) {
      constexpr int g = decltype(G)::v;
      if constexpr (g == E0 - ET) ex0 = mbar_test(bar + B_EX0, par ^ 1);
      if constexpr (g == E1 - ET) ex1 = mbar_test(bar + B_EX1, par ^ 1);
      if constexpr (g == E0) { if (!ex0) mbar_wait(bar + B_EX0, par ^ 1); fetch(IC<0>{}); }
      if constexpr (g == E1) { if (!ex1) mbar_wait(bar + B_EX1, par ^ 1); fetch(IC<1>{}); }
    };
    gemm_phase<WK, 0, false>(cb, xa, w4, rzero, [&](auto I) { ex_step(I); TSS(24 + decltype(I)::v); });
    TSB(2);
    if (k == j) {
      cluster_wait();
      mbar_wait(bar + B_KFREE, 0);
      if (j == 1) {
        wg_barrier(1);
        if (warp == 3 && elect_one()) load_w(3);
      }
      wg_wait<0>();
      TS(34);
      fence_regs(cb);
      static_for<6>([&](auto PP) { store_chunk<decltype(PP)::v>(stk + decltype(PP)::v * 256, cb); });
#pragma unroll
      for (int i = 0; i < 48; i++) ca[i] = 0.f;
      mbar_wait(sbase + B_W + 8, 0);
      TS(35);
    } else {
      gemm_phase<WO, HO, false>(ca, oo, w4, rzero, [&](auto I) {
        constexpr int s = decltype(I)::v, p = s - (HO - 1);
        if constexpr (p == -2) kfree = mbar_test(bar + B_KFREE, par);
        if constexpr (p == 0) { fence_regs(cb); TSB(3); if (!kfree) mbar_wait(bar + B_KFREE, par); }
        if constexpr (p >= 0 && p < 6) store_chunk<(p >= 0 && p < 6) ? p : 0>(stk + p * 256, cb);
        ex_step(IC<12 + s>{});
        if constexpr (s == OF || s == OF2) wg_fence();
        TSS(36 + s);
      });
    }
    gemm_phase<WQ, HQ, false>(cb, xa, w4, rzero, [&](auto I) {
      constexpr int s = decltype(I)::v, p = s - (HQ - 1);
      if constexpr (p == 0) { fence_regs(ca); TSB(4); }
      if constexpr (p >= 0 && p < 6) store_out(IC<(p >= 0 && p < 6) ? p : 0>{}, ca);
      TSS(48 + s);
    });
    if (k == j) {
      TS(36);
      mbar_wait(sbase + B_W + 16, 0);
      TS(37);
      if (j == 1) mbar_wait(sbase + B_W + 24, 0);
    }
    gemm_phase<WV, HV, true>(ca, xa, w4, rzero, [&](auto I) {
      constexpr int s = decltype(I)::v, p = s - (HV - 1);
      if constexpr (p == 0) { fence_regs(cb); TSB(6); }
      if constexpr (p >= 0 && p < 6) {
#pragma unroll
        for (int i = 4 * p; i < 4 * p + 4; i++) {
          if (i >= QT) { qf[i] = pack_bf16(cb[2 * i], cb[2 * i + 1]); continue; }
          qf[i] = oo[24 + i];
          asm("{\n.reg .pred p;\nsetp.eq.u32 p, %3, 0;\n@p cvt.rn.bf16x2.f32 %0, %1, %2;\n}\n" : "+r"(qf[i]) : "f"(cb[2 * i + 1]), "f"(cb[2 * i]), "r"(rzero));
        }
      }
      if constexpr (s == TOK) { if (l16 == 0) mbar_arrive(bar_o + B_TOKEN); }
      TSS(60 + s);
    });
    fence_regs(qf);
    fence_async_proxy();
    TSB(5);
    wg_barrier(j);
    const bool vfree = mbar_test(bar + B_VFREE, par), xfull = mbar_test(xbar, par ^ 1);
    wg_fence();
    issue_s<0>(s0, qf, k4);
    if (TOK == 12 && l16 == 0) mbar_arrive(bar_o + B_TOKEN);
    issue_s<1>(s1, qf, k4);
    if (TOK == 13 && l16 == 0) mbar_arrive(bar_o + B_TOKEN);
    TSB(7);
    send_out(wprev, k != j);
    if (l16 == 0) {
      mbar_expect_tx(bar + B_EX0, 1536);
      mbar_expect_tx(bar + B_EX1, 1536);
    }
    const int wnext = window(k + 2);
    uint32_t xaddr[4];
#pragma unroll
    for (int q = 0; q < 4; q++) xaddr[q] = xaddr0 ^ (q << 5);
    auto side = [&](auto R) {
      constexpr int r = decltype(R)::v, c = xslot(r), b = xbase(r);
      if constexpr (r == KF) {
        wg_wait<0>();
        fence_regs(s1);
        fence_regs(qf);
        if (l16 == 0) mbar_arrive(bar_o + B_KFREE);
      }
      if constexpr (r == LF) {
        asm volatile("cp.async.bulk.wait_group.read 0;" ::: "memory");
        __syncwarp();
        if (l16 == 0) mbar_arrive_remote_relaxed(r_bar + B_LFREE);
      }
      if constexpr (b == 0 && c > 0) { if (!xfull) mbar_wait(xbar, par ^ 1); TSB(19); }
      static_for<c>([&](auto J) { read_x<b + decltype(J)::v>(xa, xaddr); });
      if constexpr (r == MS) mr = mask_load(offset_ptr(mask_q + (size_t)(k + 2 < nk ? wnext : win) * 8192, l16));
      if constexpr (r == XD) {
        uint32_t all = ~0u;
#pragma unroll
        for (int i = 12 - xslot(xlast()); i < 12; i++) all &= xa[4 * i + 3];
        reads_done(all, sbase + OFF_DUMMY);
        load_tile(xdst, warp, window(k + 3), k + 3 < nk, xbar_o, &tm_x);
        TSB(15);
      }
      if constexpr (r == PFP) {
        if (k + 4 < nk) {
          const int w = window(k + 4);
          prefetch_mask(w);
          prefetch_x(w);
        }
      }
    };
    auto store_v = [&](auto PP) {
      constexpr int p = decltype(PP)::v;
      store_chunk<p>(stv + p * 2048 + (p >= 3 ? 1024 : 0), ca);
    };
    float o0[28], o1[28];
    uint32_t p0[16], p1[16];
    if (!vfree) mbar_wait(bar + B_VFREE, par);
    wg_wait<2>();
    fence_regs(ca);
    fence_regs(xa);
    TSB(8);
    store_v(IC<0>{});
    side(IC<0>{});
    store_v(IC<1>{});
    wg_wait<1>();
    fence_regs(s0);
    TSB(9);
    static_for<5>([&](auto R) {
      constexpr int r = decltype(R)::v;
      side(IC<1 + r>{});
      if constexpr (r == 0) {
        if (shifted) {
          wg_wait<0>();
          fence_regs(s1);
          uint32_t l = l16;
          asm volatile("" : "+r"(l));
          shift_logits(s0, s1, offset_ptr(mask_q + (size_t)win * 8192, (l & 0x180) * 8 + (l & 0x40) * 2 + (l & 0x30)));
        }
      }
      if constexpr (r < 4) store_v(IC<(r < 4 ? r + 2 : 0)>{});
      exponentiate<3 * r, (r < 4 ? 3 * r + 3 : 16)>(s0, eb0, p0);
      sched();
    });
    TSB(10);
    fence_async_proxy();
    exponentiate<0, NB>(s1, eb1, p1);
    sched();
    wg_barrier(j);
    side(IC<6>{});
    wg_fence();
    issue_pv<0>(o0, p0, v4);
    sched();
    TSB(11);
    static_for<4>([&](auto R) {
      constexpr int r = decltype(R)::v;
      side(IC<7 + r>{});
      exponentiate<NB + (16 - NB) * r / 4, NB + (16 - NB) * (r + 1) / 4>(s1, eb1, p1);
      if (r < 3) sched();
    });
    TSB(12);
    wg_fence();
    issue_pv<1>(o1, p1, v4);
    sched();
    side(IC<11>{});
    wg_wait<1>();
    fence_regs(o0);
    fence_regs(p0);
    TSB(13);
    uint32_t bad = normalize<0>(o0, oo);
    mbar_wait(bar + B_LFREE, par);
#pragma unroll
    for (int q = 0; q < 3; q++) st_async16(r_area + l16 + q * 512, oo[4 * q], oo[4 * q + 1], oo[4 * q + 2], oo[4 * q + 3], r_bar + B_EX0);
    TSB(14);
    side(IC<12>{});
    wg_wait<0>();
    fence_regs(o1);
    fence_regs(p1);
    TSB(16);
    if (l16 == 0) mbar_arrive(bar_o + B_VFREE);
    bad = ((bad | normalize<1>(o1, oo)) & BAD_SUM) | force;
#pragma unroll
    for (int q = 3; q < 6; q++) st_async16(r_area + l16 + q * 512, oo[4 * q], oo[4 * q + 1], oo[4 * q + 2], oo[4 * q + 3], r_bar + B_EX1);
    if (MSB) sched();
    TSB(17);
    side(IC<13>{});
    asm volatile("" : "+r"(mr.a.x), "+r"(mr.a.y), "+r"(mr.a.z), "+r"(mr.a.w), "+r"(mr.b.x), "+r"(mr.b.y), "+r"(mr.b.z), "+r"(mr.b.w),
                      "+r"(mr.c.x), "+r"(mr.c.y), "+r"(mr.c.z), "+r"(mr.c.w), "+r"(mr.d.x), "+r"(mr.d.y), "+r"(mr.d.z), "+r"(mr.d.w)::"memory");
    shifted = __any_sync(0xffffffffu, (mask_or(mr) | bad) != 0);
    if (shifted && __any_sync(0xffffffffu, (bad & BAD_SUM) != 0)) {
      force |= 1;
      if ((l16 >> 4) == (uint32_t)(k >> 6)) asm volatile("red.shared.or.b32 [%0], %1;" ::"r"(sbase + OFF_FAIL + 512 * j + 128 * warp + (l16 >> 2)), "r"(1u << ((k >> 1) & 31)) : "memory");
    }
    wprev = win;
    win = wnext;
    k += 2;
    if (k >= nk) break;
    par ^= 1;
    TSB(18);
    TS_SET(k);
    TSB(0);
    mbar_wait(bar + B_TOKEN, par);
  }
  {
    const uint32_t a = sbase + OFF_FAIL + 512 * j + 128 * warp + (l16 >> 2);
    asm volatile("st.async.weak.shared::cluster.mbarrier::complete_tx::bytes.b32 [%0], %1, [%2];" ::"r"(mapa(a + 1024, peer)), "r"(lds32(a)), "r"(mapa(sbase + B_DONE, peer)) : "memory");
    __syncwarp();
    if (l16 == 0) mbar_expect_tx(sbase + B_DONE, 128);
  }
  {
    float ca[48];
    mbar_wait(sbase + B_W + 24, 0);
    gemm_phase<WO, 0, false>(ca, oo, w4, rzero, [&](auto I) {
      constexpr int s = decltype(I)::v;
      if constexpr (s == 5) { mbar_wait(bar + B_EX0, par); fetch(IC<0>{}); wg_fence(); }
      if constexpr (s == 8) { mbar_wait(bar + B_EX1, par); fetch(IC<1>{}); wg_fence(); }
    });
    wg_wait<0>();
    fence_regs(ca);
    fence_regs(oo);
    static_for<6>([&](auto PP) { store_out(PP, ca); });
    fence_async_proxy();
    __syncwarp();
    send_out(wprev, true);
  }
  TS(21);
  if (k == nk + 1) mbar_wait(xbar_o, j ? par : par ^ 1);
  mbar_wait(sbase + B_DONE, 0);
  uint32_t failed = 0;
#pragma unroll
  for (int i = 0; i < 4; i++) {
    const uint4 f = lds128(sbase + OFF_FAIL + 512 * i + l16);
    failed |= f.x | f.y | f.z | f.w;
  }
  if (__any_sync(0xffffffffu, failed != 0)) {
    asm volatile("cp.async.bulk.wait_group 0;" ::: "memory");
    asm volatile("fence.proxy.async;" ::: "memory");
    for (int kk = 0; kk < nk; kk++) {
      uint32_t f = 0;
      for (int i = 0; i < 8; i++) f |= lds32(sbase + OFF_FAIL + 1024 * (i >> 2) + 512 * (kk & 1) + 128 * (i & 3) + 4 * (kk >> 6));
      if ((f >> ((kk >> 1) & 31)) & 1) redo_window(P, reinterpret_cast<float*>(smem_raw), window_any(kk), rank);
    }
  }
  asm volatile("cp.async.bulk.wait_group.read 0;" ::: "memory");
  TS(22);
}

typedef CUresult (*EncodeTiledFn)(CUtensorMap*, CUtensorMapDataType, cuuint32_t, void*, const cuuint64_t*, const cuuint64_t*,
                                  const cuuint32_t*, const cuuint32_t*, CUtensorMapInterleave, CUtensorMapSwizzle,
                                  CUtensorMapL2promotion, CUtensorMapFloatOOBfill);

void encode_image_map(EncodeTiledFn fn, CUtensorMap* tm, void* ptr, uint32_t group_c, CUtensorMapSwizzle sw) {
  const cuuint64_t dims[5] = {(cuuint64_t)group_c, 2, (cuuint64_t)IMG, (cuuint64_t)IMG / 2, (cuuint64_t)(CH / group_c)};
  const cuuint64_t strides[4] = {(cuuint64_t)CH * 2, (cuuint64_t)CH * 2 * IMG, (cuuint64_t)CH * 4, (cuuint64_t)group_c * 2};
  const cuuint32_t box[5] = {group_c, 2, 4, 2, 3};
  const cuuint32_t estr[5] = {1, 1, 1, 1, 1};
  fn(tm, CU_TENSOR_MAP_DATA_TYPE_BFLOAT16, 5, ptr, dims, strides, box, estr, CU_TENSOR_MAP_INTERLEAVE_NONE, sw,
     CU_TENSOR_MAP_L2_PROMOTION_L2_128B, CU_TENSOR_MAP_FLOAT_OOB_FILL_NONE);
}
void encode_weight_map(EncodeTiledFn fn, CUtensorMap* tm, void* ptr, uint32_t cols) {
  const cuuint64_t dims[3] = {32, (cuuint64_t)CH, (cuuint64_t)(cols / 32)};
  const cuuint64_t strides[2] = {(cuuint64_t)cols * 2, 64};
  const cuuint32_t box[3] = {32, 96, 3};
  const cuuint32_t estr[3] = {1, 1, 1};
  fn(tm, CU_TENSOR_MAP_DATA_TYPE_BFLOAT16, 3, ptr, dims, strides, box, estr, CU_TENSOR_MAP_INTERLEAVE_NONE, CU_TENSOR_MAP_SWIZZLE_64B,
     CU_TENSOR_MAP_L2_PROMOTION_L2_128B, CU_TENSOR_MAP_FLOAT_OOB_FILL_NONE);
}

}

extern "C" void kernel_launch(void* const* d_in, const int* in_sizes, int n_in, void* d_out, int out_size) {
  (void)in_sizes; (void)n_in; (void)out_size;
  static int nclusters = 0;
  static EncodeTiledFn encode = nullptr;
  if (nclusters == 0) {
    cudaFuncSetAttribute(swin_attn_kernel, cudaFuncAttributeMaxDynamicSharedMemorySize, SMEM_BYTES);
    int dev = 0, sms = 0;
    cudaGetDevice(&dev);
    cudaDeviceGetAttribute(&sms, cudaDevAttrMultiProcessorCount, dev);
    nclusters = sms / 2;
    cudaLaunchConfig_t cfg = {};
    cfg.gridDim = dim3(2 * nclusters);
    cfg.blockDim = dim3(THREADS);
    cfg.dynamicSmemBytes = SMEM_BYTES;
    cudaLaunchAttribute at[1];
    at[0].id = cudaLaunchAttributeClusterDimension;
    at[0].val.clusterDim.x = 2; at[0].val.clusterDim.y = 1; at[0].val.clusterDim.z = 1;
    cfg.attrs = at; cfg.numAttrs = 1;
    int maxc = 0;
    if (cudaOccupancyMaxActiveClusters(&maxc, swin_attn_kernel, &cfg) == cudaSuccess && maxc > 0 && maxc < nclusters) nclusters = maxc;
    (void)cudaGetLastError();
    void* fn = nullptr;
    cudaDriverEntryPointQueryResult qres;
    cudaGetDriverEntryPoint("cuTensorMapEncodeTiled", &fn, cudaEnableDefault, &qres);
    encode = (EncodeTiledFn)fn;
  }
  CUtensorMap tm_x, tm_o, tm_w, tm_wo;
  encode_image_map(encode, &tm_x, d_in[0], 64, CU_TENSOR_MAP_SWIZZLE_128B);
  encode_image_map(encode, &tm_o, d_out, 32, CU_TENSOR_MAP_SWIZZLE_64B);
  encode_weight_map(encode, &tm_w, d_in[1], 3 * CH);
  encode_weight_map(encode, &tm_wo, d_in[2], CH);
  Params P;
  P.x = (const __nv_bfloat16*)d_in[0];
  P.wqkv = (const __nv_bfloat16*)d_in[1];
  P.wo = (const __nv_bfloat16*)d_in[2];
  P.rpb = (const __nv_bfloat16*)d_in[3];
  P.rp_idx = (const int*)d_in[4];
  P.mask = (const __nv_bfloat16*)d_in[5];
  P.out = (__nv_bfloat16*)d_out;
  P.nclusters = nclusters;
  P.nk_min = NWIN / nclusters;
  P.nk_rem = NWIN % nclusters;
  swin_attn_kernel<<<2 * nclusters, THREADS, SMEM_BYTES, cudaStreamPerThread>>>(tm_x, tm_o, tm_w, tm_wo, P);
}
```

```cpp
#include <cuda_runtime.h>
#include <cuda_bf16.h>
#include <cuda.h>
#include <stdint.h>

namespace {

constexpr int IMG = 512, CH = 192, NWIN = 4096;
constexpr int THREADS = 256;
#define ONES 0
constexpr int NO = ONES ? 28 : 24;

constexpr uint32_t OFF_X = 0;
constexpr uint32_t OFF_K = 24576;
constexpr uint32_t UB = 1536;
constexpr uint32_t OFF_V = OFF_K + 12288;
constexpr uint32_t OFF_L = OFF_V + 13 * 1024;
constexpr uint32_t OFF_W = OFF_L + 2 * 12288;
constexpr uint32_t W_HALF = 3 * 96 * 64, W_PART = 2 * W_HALF;
constexpr uint32_t WK = OFF_W, WQ = OFF_W + W_PART, WV = OFF_W + 2 * W_PART, WO = OFF_W + 3 * W_PART;
constexpr uint32_t OFF_BAR = OFF_W + 4 * W_PART;
constexpr uint32_t B_XFULL = 0;
constexpr uint32_t B_TOKEN = 32;
constexpr uint32_t B_KFREE = 40, B_VFREE = 48;
constexpr uint32_t B_EX0 = 56, B_EX1 = 64;
constexpr uint32_t B_LFREE = 72;
constexpr uint32_t B_X1 = 80;
constexpr uint32_t B_W = OFF_BAR + 256;
constexpr uint32_t B_IDX = OFF_BAR + 296;
constexpr uint32_t B_DONE = OFF_BAR + 304;
constexpr uint32_t OFF_DUMMY = OFF_BAR + 320;
constexpr uint32_t OFF_FAIL = OFF_BAR + 384;
constexpr uint32_t OFF_TAB = OFF_FAIL + 2048;
constexpr uint32_t OFF_TS = OFF_TAB + 1024;
constexpr uint32_t SMEM_BYTES = OFF_TS;

constexpr float LOG2E = 1.4426950408889634f;
constexpr float SCALE = 0.14433756729740643f;

__device__ __forceinline__ uint32_t smem_u32(const void* p) { return (uint32_t)__cvta_generic_to_shared(p); }
__device__ __forceinline__ void wg_fence() { asm volatile("wgmma.fence.sync.aligned;" ::: "memory"); }
__device__ __forceinline__ void wg_commit() { asm volatile("wgmma.commit_group.sync.aligned;" ::: "memory"); }
template <int N> __device__ __forceinline__ void wg_wait() { asm volatile("wgmma.wait_group.sync.aligned %0;" ::"n"(N) : "memory"); }
template <int N> __device__ __forceinline__ void fence_regs(float (&d)[N]) {
#pragma unroll
  for (int i = 0; i < N; i++) asm volatile("" : "+f"(d[i])::"memory");
}
template <int N> __device__ __forceinline__ void fence_regs(uint32_t (&d)[N]) {
#pragma unroll
  for (int i = 0; i < N; i++) asm volatile("" : "+r"(d[i])::"memory");
}
__device__ __forceinline__ bool elect_one() {
  uint32_t pred;
  asm volatile("{\n.reg .pred p;\nelect.sync _|p, 0xffffffff;\nselp.u32 %0, 1, 0, p;\n}\n" : "=r"(pred));
  return pred != 0;
}
__device__ __forceinline__ uint32_t pack_bf16(float lo, float hi) {
  uint32_t r;
  asm("cvt.rn.bf16x2.f32 %0, %1, %2;" : "=r"(r) : "f"(hi), "f"(lo));
  return r;
}
__device__ __forceinline__ float bf_lo(uint32_t v) { return __uint_as_float(v << 16); }
__device__ __forceinline__ float bf_hi(uint32_t v) { return __uint_as_float(v & 0xffff0000u); }
__device__ __forceinline__ float ex2(float x) {
  float y;
  asm("ex2.approx.ftz.f32 %0, %1;" : "=f"(y) : "f"(x));
  return y;
}
__device__ __forceinline__ uint32_t hadd2(uint32_t a, uint32_t b) {
  uint32_t r;
  asm("add.rn.bf16x2 %0, %1, %2;" : "=r"(r) : "r"(a), "r"(b));
  return r;
}
__device__ __forceinline__ uint32_t hmul2(uint32_t a, uint32_t b) {
  uint32_t r;
  asm("mul.rn.bf16x2 %0, %1, %2;" : "=r"(r) : "r"(a), "r"(b));
  return r;
}
__device__ __forceinline__ uint32_t dup_lo(uint32_t a) {
  uint32_t r;
  asm("{\n.reg .b16 l, h;\nmov.b32 {l, h}, %1;\nmov.b32 %0, {l, l};\n}\n" : "=r"(r) : "r"(a));
  return r;
}
__device__ __forceinline__ uint32_t dup_hi(uint32_t a) {
  uint32_t r;
  asm("{\n.reg .b16 l, h;\nmov.b32 {l, h}, %1;\nmov.b32 %0, {h, h};\n}\n" : "=r"(r) : "r"(a));
  return r;
}
__device__ __forceinline__ float rcp_approx(float x) {
  float y;
  asm("rcp.approx.ftz.f32 %0, %1;" : "=f"(y) : "f"(x));
  return y;
}
__device__ __forceinline__ uint4 ldg128(const void* p) {
  uint4 v;
  asm volatile("ld.global.L1::evict_normal.v4.u32 {%0,%1,%2,%3}, [%4];" : "=r"(v.x), "=r"(v.y), "=r"(v.z), "=r"(v.w) : "l"(p) : "memory");
  return v;
}
__device__ __forceinline__ void prefetch_l2(const void* p, uint32_t bytes) {
  asm volatile("cp.async.bulk.prefetch.L2.global [%0], %1;" ::"l"(p), "r"(bytes) : "memory");
}
__device__ __forceinline__ uint4 lds128(uint32_t addr) {
  uint4 v;
  asm volatile("ld.shared.v4.u32 {%0,%1,%2,%3}, [%4];" : "=r"(v.x), "=r"(v.y), "=r"(v.z), "=r"(v.w) : "r"(addr) : "memory");
  return v;
}
__device__ __forceinline__ uint4 lds128v(uint32_t addr) {
  uint4 v;
  asm volatile("ld.volatile.shared.v4.u32 {%0,%1,%2,%3}, [%4];" : "=r"(v.x), "=r"(v.y), "=r"(v.z), "=r"(v.w) : "r"(addr) : "memory");
  return v;
}
__device__ __forceinline__ uint32_t lds32(uint32_t addr) {
  uint32_t v;
  asm volatile("ld.shared.u32 %0, [%1];" : "=r"(v) : "r"(addr) : "memory");
  return v;
}
__device__ __forceinline__ void stmatrix_x4(uint32_t addr, uint32_t a, uint32_t b, uint32_t c, uint32_t d) {
  asm volatile("stmatrix.sync.aligned.m8n8.x4.shared.b16 [%0], {%1,%2,%3,%4};" ::"r"(addr), "r"(a), "r"(b), "r"(c), "r"(d) : "memory");
}
__device__ __forceinline__ void ldmatrix_x4(uint32_t addr, uint32_t& a, uint32_t& b, uint32_t& c, uint32_t& d) {
  asm volatile("ldmatrix.sync.aligned.m8n8.x4.shared.b16 {%0,%1,%2,%3}, [%4];" : "=r"(a), "=r"(b), "=r"(c), "=r"(d) : "r"(addr) : "memory");
}
__device__ __forceinline__ void fence_async_proxy() {
  asm volatile("fence.proxy.async.shared::cta;" ::: "memory");
}
constexpr int N_TOKEN = 3, N_KFREE = 5, N_VFREE = 7;
__device__ __forceinline__ void wg_barrier(int j) { asm volatile("bar.sync %0, 128;" ::"r"(1 + j) : "memory"); }
__device__ __forceinline__ void hand_over(int id) { asm volatile("bar.arrive %0, 256;" ::"r"(id) : "memory"); }
__device__ __forceinline__ void take_over(int id) { asm volatile("bar.sync %0, 256;" ::"r"(id) : "memory"); }
__device__ __forceinline__ void cluster_wait() { asm volatile("barrier.cluster.wait.acquire.aligned;" ::: "memory"); }
__device__ __forceinline__ uint32_t mapa(uint32_t a, uint32_t rank) {
  uint32_t o;
  asm("mapa.shared::cluster.u32 %0, %1, %2;" : "=r"(o) : "r"(a), "r"(rank));
  return o;
}
__device__ __forceinline__ void mbar_init(uint32_t a, uint32_t cnt) { asm volatile("mbarrier.init.shared::cta.b64 [%0], %1;" ::"r"(a), "r"(cnt) : "memory"); }
__device__ __forceinline__ void mbar_expect_tx(uint32_t a, uint32_t tx) {
  asm volatile("mbarrier.arrive.expect_tx.shared::cta.b64 _, [%0], %1;" ::"r"(a), "r"(tx) : "memory");
}
__device__ __forceinline__ void mbar_arrive(uint32_t a) { asm volatile("mbarrier.arrive.shared::cta.b64 _, [%0];" ::"r"(a) : "memory"); }
__device__ __forceinline__ void mbar_arrive4(uint32_t a) { asm volatile("mbarrier.arrive.shared::cta.b64 _, [%0], 4;" ::"r"(a) : "memory"); }
__device__ __forceinline__ uint32_t uniform(uint32_t v) { return __shfl_sync(0xffffffffu, v, 0); }
__device__ __forceinline__ void mbar_arrive_remote_relaxed(uint32_t a) {
  asm volatile("mbarrier.arrive.relaxed.cluster.shared::cluster.b64 _, [%0];" ::"r"(a) : "memory");
}
__device__ __forceinline__ void mbar_wait(uint32_t a, uint32_t parity) {
  asm volatile(
      "{\n.reg .pred p;\n.reg .u32 n;\n"
      "mbarrier.try_wait.parity.shared::cta.b64 p, [%0], %1;\n"
      "@p bra WAIT_DONE;\n"
      "mov.u32 n, 0;\n"
      "WAIT_LOOP:\n"
      "add.u32 n, n, 1;\n"
      "setp.gt.u32 p, n, 4000000;\n"
      "@p trap;\n"
      "mbarrier.try_wait.parity.shared::cta.b64 p, [%0], %1;\n"
      "@!p bra WAIT_LOOP;\n"
      "WAIT_DONE:\n}\n" ::"r"(a), "r"(parity) : "memory");
}
__device__ __forceinline__ bool mbar_test(uint32_t a, uint32_t parity) {
  uint32_t ok;
  asm volatile("{\n.reg .pred p;\nmbarrier.test_wait.parity.shared::cta.b64 p, [%1], %2;\nselp.u32 %0, 1, 0, p;\n}\n" : "=r"(ok) : "r"(a), "r"(parity) : "memory");
  return ok != 0;
}
__device__ __forceinline__ uint32_t hfma2(uint32_t a, uint32_t b, uint32_t c) {
  uint32_t r;
  asm("fma.rn.bf16x2 %0, %1, %2, %3;" : "=r"(r) : "r"(a), "r"(b), "r"(c));
  return r;
}
__device__ __forceinline__ void st_async16(uint32_t raddr, uint32_t a, uint32_t b, uint32_t c, uint32_t d, uint32_t rbar) {
  asm volatile("st.async.weak.shared::cluster.mbarrier::complete_tx::bytes.v4.b32 [%0], {%1,%2,%3,%4}, [%5];" ::"r"(raddr),
               "r"(a), "r"(b), "r"(c), "r"(d), "r"(rbar) : "memory");
}

__device__ __forceinline__ void sts128(uint32_t addr, uint4 v) {
  asm volatile("st.shared.v4.u32 [%0], {%1,%2,%3,%4};" ::"r"(addr), "r"(v.x), "r"(v.y), "r"(v.z), "r"(v.w) : "memory");
}
__device__ __forceinline__ void bulk_load(uint32_t dst, const void* src, uint32_t bytes, uint32_t bar) {
  asm volatile("cp.async.bulk.shared::cta.global.mbarrier::complete_tx::bytes [%0], [%1], %2, [%3];" ::"r"(dst), "l"(src),
               "r"(bytes), "r"(bar) : "memory");
}
__device__ __forceinline__ void tma_load3(uint32_t dst, const CUtensorMap* tm, int c1, int c2, uint32_t bar) {
  asm volatile("cp.async.bulk.tensor.3d.shared::cta.global.tile.mbarrier::complete_tx::bytes [%0], [%1, {0, %2, %3}], [%4];" ::"r"(dst),
               "l"(tm), "r"(c1), "r"(c2), "r"(bar) : "memory");
}
__device__ __forceinline__ void tma_load5(uint32_t dst, const CUtensorMap* tm, int c2, int c3, uint32_t bar) {
  asm volatile("cp.async.bulk.tensor.5d.shared::cta.global.tile.mbarrier::complete_tx::bytes [%0], [%1, {0, 0, %2, %3, 0}], [%4];" ::"r"(dst),
               "l"(tm), "r"(c2), "r"(c3), "r"(bar) : "memory");
}
__device__ __forceinline__ void tma_prefetch5(const CUtensorMap* tm, int c2, int c3) {
  asm volatile("cp.async.bulk.prefetch.tensor.5d.L2.global.tile [%0, {0, 0, %1, %2, 0}];" ::"l"(tm), "r"(c2), "r"(c3) : "memory");
}
__device__ __forceinline__ void tma_store5(const CUtensorMap* tm, int c2, int c3, int c4, uint32_t src) {
  asm volatile("cp.async.bulk.tensor.5d.global.shared::cta.tile.bulk_group [%0, {0, 0, %1, %2, %3}], [%4];" ::"l"(tm), "r"(c2), "r"(c3),
               "r"(c4), "r"(src) : "memory");
}
__device__ __forceinline__ void sched_barrier(uint32_t& t, uint32_t zero) {
  asm volatile("{\n.reg .pred p;\nsetp.ne.u32 p, %1, 0;\n@p mov.u32 %0, %%clock;\n}\n" : "+r"(t) : "r"(zero) : "memory");
}

#define TS(i)
#define TS_SET(k)
#define TSS(i)
__device__ __forceinline__ void wgmma_n48_a(float (&d)[24], uint32_t a0, uint32_t a1, uint32_t a2, uint32_t a3, uint64_t db) {
  asm volatile("{\n.reg .pred p;\nsetp.ne.b32 p, 1, 0;\n"
      "wgmma.mma_async.sync.aligned.m64n48k16.f32.bf16.bf16 "
      "{%0,%1,%2,%3,%4,%5,%6,%7,%8,%9,%10,%11,%12,%13,%14,%15,"
      "%16,%17,%18,%19,%20,%21,%22,%23}, "
      "{%24,%25,%26,%27}, %28, p, 1, 1, 1;\n}\n"
      : "+f"(d[0]), "+f"(d[1]), "+f"(d[2]), "+f"(d[3]), "+f"(d[4]), "+f"(d[5]), "+f"(d[6]), "+f"(d[7]),
        "+f"(d[8]), "+f"(d[9]), "+f"(d[10]), "+f"(d[11]), "+f"(d[12]), "+f"(d[13]), "+f"(d[14]), "+f"(d[15]),
        "+f"(d[16]), "+f"(d[17]), "+f"(d[18]), "+f"(d[19]), "+f"(d[20]), "+f"(d[21]), "+f"(d[22]), "+f"(d[23])
      : "r"(a0), "r"(a1), "r"(a2), "r"(a3), "l"(db));
}
__device__ __forceinline__ void wgmma_n48_z(float (&d)[24], uint32_t a0, uint32_t a1, uint32_t a2, uint32_t a3, uint64_t db) {
  asm volatile("{\n.reg .pred p;\nsetp.ne.b32 p, 0, 0;\n"
      "wgmma.mma_async.sync.aligned.m64n48k16.f32.bf16.bf16 "
      "{%0,%1,%2,%3,%4,%5,%6,%7,%8,%9,%10,%11,%12,%13,%14,%15,"
      "%16,%17,%18,%19,%20,%21,%22,%23}, "
      "{%24,%25,%26,%27}, %28, p, 1, 1, 1;\n}\n"
      : "=f"(d[0]), "=f"(d[1]), "=f"(d[2]), "=f"(d[3]), "=f"(d[4]), "=f"(d[5]), "=f"(d[6]), "=f"(d[7]),
        "=f"(d[8]), "=f"(d[9]), "=f"(d[10]), "=f"(d[11]), "=f"(d[12]), "=f"(d[13]), "=f"(d[14]), "=f"(d[15]),
        "=f"(d[16]), "=f"(d[17]), "=f"(d[18]), "=f"(d[19]), "=f"(d[20]), "=f"(d[21]), "=f"(d[22]), "=f"(d[23])
      : "r"(a0), "r"(a1), "r"(a2), "r"(a3), "l"(db));
}
__device__ __forceinline__ void wgmma_n56_a(float (&d)[28], uint32_t a0, uint32_t a1, uint32_t a2, uint32_t a3, uint64_t db) {
  asm volatile("{\n.reg .pred p;\nsetp.ne.b32 p, 1, 0;\n"
      "wgmma.mma_async.sync.aligned.m64n56k16.f32.bf16.bf16 "
      "{%0,%1,%2,%3,%4,%5,%6,%7,%8,%9,%10,%11,%12,%13,%14,%15,"
      "%16,%17,%18,%19,%20,%21,%22,%23,%24,%25,%26,%27}, "
      "{%28,%29,%30,%31}, %32, p, 1, 1, 1;\n}\n"
      : "+f"(d[0]), "+f"(d[1]), "+f"(d[2]), "+f"(d[3]), "+f"(d[4]), "+f"(d[5]), "+f"(d[6]), "+f"(d[7]),
        "+f"(d[8]), "+f"(d[9]), "+f"(d[10]), "+f"(d[11]), "+f"(d[12]), "+f"(d[13]), "+f"(d[14]), "+f"(d[15]),
        "+f"(d[16]), "+f"(d[17]), "+f"(d[18]), "+f"(d[19]), "+f"(d[20]), "+f"(d[21]), "+f"(d[22]), "+f"(d[23]),
        "+f"(d[24]), "+f"(d[25]), "+f"(d[26]), "+f"(d[27])
      : "r"(a0), "r"(a1), "r"(a2), "r"(a3), "l"(db));
}
__device__ __forceinline__ void wgmma_n56_z(float (&d)[28], uint32_t a0, uint32_t a1, uint32_t a2, uint32_t a3, uint64_t db) {
  asm volatile("{\n.reg .pred p;\nsetp.ne.b32 p, 0, 0;\n"
      "wgmma.mma_async.sync.aligned.m64n56k16.f32.bf16.bf16 "
      "{%0,%1,%2,%3,%4,%5,%6,%7,%8,%9,%10,%11,%12,%13,%14,%15,"
      "%16,%17,%18,%19,%20,%21,%22,%23,%24,%25,%26,%27}, "
      "{%28,%29,%30,%31}, %32, p, 1, 1, 1;\n}\n"
      : "=f"(d[0]), "=f"(d[1]), "=f"(d[2]), "=f"(d[3]), "=f"(d[4]), "=f"(d[5]), "=f"(d[6]), "=f"(d[7]),
        "=f"(d[8]), "=f"(d[9]), "=f"(d[10]), "=f"(d[11]), "=f"(d[12]), "=f"(d[13]), "=f"(d[14]), "=f"(d[15]),
        "=f"(d[16]), "=f"(d[17]), "=f"(d[18]), "=f"(d[19]), "=f"(d[20]), "=f"(d[21]), "=f"(d[22]), "=f"(d[23]),
        "=f"(d[24]), "=f"(d[25]), "=f"(d[26]), "=f"(d[27])
      : "r"(a0), "r"(a1), "r"(a2), "r"(a3), "l"(db));
}
__device__ __forceinline__ void wgmma_n96_a(float (&d)[48], uint32_t a0, uint32_t a1, uint32_t a2, uint32_t a3, uint64_t db) {
  asm volatile("{\n.reg .pred p;\nsetp.ne.b32 p, 1, 0;\n"
      "wgmma.mma_async.sync.aligned.m64n96k16.f32.bf16.bf16 "
      "{%0,%1,%2,%3,%4,%5,%6,%7,%8,%9,%10,%11,%12,%13,%14,%15,"
      "%16,%17,%18,%19,%20,%21,%22,%23,%24,%25,%26,%27,%28,%29,%30,%31,"
      "%32,%33,%34,%35,%36,%37,%38,%39,%40,%41,%42,%43,%44,%45,%46,%47}, "
      "{%48,%49,%50,%51}, %52, p, 1, 1, 1;\n}\n"
      : "+f"(d[0]), "+f"(d[1]), "+f"(d[2]), "+f"(d[3]), "+f"(d[4]), "+f"(d[5]), "+f"(d[6]), "+f"(d[7]),
        "+f"(d[8]), "+f"(d[9]), "+f"(d[10]), "+f"(d[11]), "+f"(d[12]), "+f"(d[13]), "+f"(d[14]), "+f"(d[15]),
        "+f"(d[16]), "+f"(d[17]), "+f"(d[18]), "+f"(d[19]), "+f"(d[20]), "+f"(d[21]), "+f"(d[22]), "+f"(d[23]),
        "+f"(d[24]), "+f"(d[25]), "+f"(d[26]), "+f"(d[27]), "+f"(d[28]), "+f"(d[29]), "+f"(d[30]), "+f"(d[31]),
        "+f"(d[32]), "+f"(d[33]), "+f"(d[34]), "+f"(d[35]), "+f"(d[36]), "+f"(d[37]), "+f"(d[38]), "+f"(d[39]),
        "+f"(d[40]), "+f"(d[41]), "+f"(d[42]), "+f"(d[43]), "+f"(d[44]), "+f"(d[45]), "+f"(d[46]), "+f"(d[47])
      : "r"(a0), "r"(a1), "r"(a2), "r"(a3), "l"(db));
}
__device__ __forceinline__ void wgmma_n96_z(float (&d)[48], uint32_t a0, uint32_t a1, uint32_t a2, uint32_t a3, uint64_t db) {
  asm volatile("{\n.reg .pred p;\nsetp.ne.b32 p, 0, 0;\n"
      "wgmma.mma_async.sync.aligned.m64n96k16.f32.bf16.bf16 "
      "{%0,%1,%2,%3,%4,%5,%6,%7,%8,%9,%10,%11,%12,%13,%14,%15,"
      "%16,%17,%18,%19,%20,%21,%22,%23,%24,%25,%26,%27,%28,%29,%30,%31,"
      "%32,%33,%34,%35,%36,%37,%38,%39,%40,%41,%42,%43,%44,%45,%46,%47}, "
      "{%48,%49,%50,%51}, %52, p, 1, 1, 1;\n}\n"
      : "=f"(d[0]), "=f"(d[1]), "=f"(d[2]), "=f"(d[3]), "=f"(d[4]), "=f"(d[5]), "=f"(d[6]), "=f"(d[7]),
        "=f"(d[8]), "=f"(d[9]), "=f"(d[10]), "=f"(d[11]), "=f"(d[12]), "=f"(d[13]), "=f"(d[14]), "=f"(d[15]),
        "=f"(d[16]), "=f"(d[17]), "=f"(d[18]), "=f"(d[19]), "=f"(d[20]), "=f"(d[21]), "=f"(d[22]), "=f"(d[23]),
        "=f"(d[24]), "=f"(d[25]), "=f"(d[26]), "=f"(d[27]), "=f"(d[28]), "=f"(d[29]), "=f"(d[30]), "=f"(d[31]),
        "=f"(d[32]), "=f"(d[33]), "=f"(d[34]), "=f"(d[35]), "=f"(d[36]), "=f"(d[37]), "=f"(d[38]), "=f"(d[39]),
        "=f"(d[40]), "=f"(d[41]), "=f"(d[42]), "=f"(d[43]), "=f"(d[44]), "=f"(d[45]), "=f"(d[46]), "=f"(d[47])
      : "r"(a0), "r"(a1), "r"(a2), "r"(a3), "l"(db));
}
__device__ __forceinline__ void wgmma_n96_p(float (&d)[48], uint32_t a0, uint32_t a1, uint32_t a2, uint32_t a3, uint64_t db, uint32_t acc) {
  asm volatile("{\n.reg .pred p;\nsetp.ne.b32 p, %53, 0;\n"
      "wgmma.mma_async.sync.aligned.m64n96k16.f32.bf16.bf16 "
      "{%0,%1,%2,%3,%4,%5,%6,%7,%8,%9,%10,%11,%12,%13,%14,%15,"
      "%16,%17,%18,%19,%20,%21,%22,%23,%24,%25,%26,%27,%28,%29,%30,%31,"
      "%32,%33,%34,%35,%36,%37,%38,%39,%40,%41,%42,%43,%44,%45,%46,%47}, "
      "{%48,%49,%50,%51}, %52, p, 1, 1, 1;\n}\n"
      : "+f"(d[0]), "+f"(d[1]), "+f"(d[2]), "+f"(d[3]), "+f"(d[4]), "+f"(d[5]), "+f"(d[6]), "+f"(d[7]),
        "+f"(d[8]), "+f"(d[9]), "+f"(d[10]), "+f"(d[11]), "+f"(d[12]), "+f"(d[13]), "+f"(d[14]), "+f"(d[15]),
        "+f"(d[16]), "+f"(d[17]), "+f"(d[18]), "+f"(d[19]), "+f"(d[20]), "+f"(d[21]), "+f"(d[22]), "+f"(d[23]),
        "+f"(d[24]), "+f"(d[25]), "+f"(d[26]), "+f"(d[27]), "+f"(d[28]), "+f"(d[29]), "+f"(d[30]), "+f"(d[31]),
        "+f"(d[32]), "+f"(d[33]), "+f"(d[34]), "+f"(d[35]), "+f"(d[36]), "+f"(d[37]), "+f"(d[38]), "+f"(d[39]),
        "+f"(d[40]), "+f"(d[41]), "+f"(d[42]), "+f"(d[43]), "+f"(d[44]), "+f"(d[45]), "+f"(d[46]), "+f"(d[47])
      : "r"(a0), "r"(a1), "r"(a2), "r"(a3), "l"(db), "r"(acc));
}
__device__ __forceinline__ void wgmma_n64_a(float (&d)[32], uint32_t a0, uint32_t a1, uint32_t a2, uint32_t a3, uint64_t db) {
  asm volatile("{\n.reg .pred p;\nsetp.ne.b32 p, 1, 0;\n"
      "wgmma.mma_async.sync.aligned.m64n64k16.f32.bf16.bf16 "
      "{%0,%1,%2,%3,%4,%5,%6,%7,%8,%9,%10,%11,%12,%13,%14,%15,"
      "%16,%17,%18,%19,%20,%21,%22,%23,%24,%25,%26,%27,%28,%29,%30,%31}, "
      "{%32,%33,%34,%35}, %36, p, 1, 1, 0;\n}\n"
      : "+f"(d[0]), "+f"(d[1]), "+f"(d[2]), "+f"(d[3]), "+f"(d[4]), "+f"(d[5]), "+f"(d[6]), "+f"(d[7]),
        "+f"(d[8]), "+f"(d[9]), "+f"(d[10]), "+f"(d[11]), "+f"(d[12]), "+f"(d[13]), "+f"(d[14]), "+f"(d[15]),
        "+f"(d[16]), "+f"(d[17]), "+f"(d[18]), "+f"(d[19]), "+f"(d[20]), "+f"(d[21]), "+f"(d[22]), "+f"(d[23]),
        "+f"(d[24]), "+f"(d[25]), "+f"(d[26]), "+f"(d[27]), "+f"(d[28]), "+f"(d[29]), "+f"(d[30]), "+f"(d[31])
      : "r"(a0), "r"(a1), "r"(a2), "r"(a3), "l"(db));
}
__device__ __forceinline__ void wgmma_n64_z(float (&d)[32], uint32_t a0, uint32_t a1, uint32_t a2, uint32_t a3, uint64_t db) {
  asm volatile("{\n.reg .pred p;\nsetp.ne.b32 p, 0, 0;\n"
      "wgmma.mma_async.sync.aligned.m64n64k16.f32.bf16.bf16 "
      "{%0,%1,%2,%3,%4,%5,%6,%7,%8,%9,%10,%11,%12,%13,%14,%15,"
      "%16,%17,%18,%19,%20,%21,%22,%23,%24,%25,%26,%27,%28,%29,%30,%31}, "
      "{%32,%33,%34,%35}, %36, p, 1, 1, 0;\n}\n"
      : "=f"(d[0]), "=f"(d[1]), "=f"(d[2]), "=f"(d[3]), "=f"(d[4]), "=f"(d[5]), "=f"(d[6]), "=f"(d[7]),
        "=f"(d[8]), "=f"(d[9]), "=f"(d[10]), "=f"(d[11]), "=f"(d[12]), "=f"(d[13]), "=f"(d[14]), "=f"(d[15]),
        "=f"(d[16]), "=f"(d[17]), "=f"(d[18]), "=f"(d[19]), "=f"(d[20]), "=f"(d[21]), "=f"(d[22]), "=f"(d[23]),
        "=f"(d[24]), "=f"(d[25]), "=f"(d[26]), "=f"(d[27]), "=f"(d[28]), "=f"(d[29]), "=f"(d[30]), "=f"(d[31])
      : "r"(a0), "r"(a1), "r"(a2), "r"(a3), "l"(db));
}

template <uint32_t OFF, uint32_t LBO>
__device__ __forceinline__ uint64_t desc_at(uint64_t base) {
  return base + (uint64_t)((OFF >> 4) + ((LBO >> 4) << 16));
}
template <uint32_t SBO, uint32_t SWIZZLE = 0>
__device__ __forceinline__ uint64_t desc_base(uint32_t addr4) {
  return ((uint64_t)SWIZZLE << 62) | ((uint64_t)(SBO >> 4) << 32) | (uint64_t)addr4;
}
__device__ __forceinline__ uint64_t pin(uint64_t v) {
  asm volatile("" : "+l"(v));
  return v;
}
template <int I> struct IC { static constexpr int v = I; };
template <int N, class F> __device__ __forceinline__ void static_for(F&& f) {
  if constexpr (N > 0) { static_for<N - 1>(f); f(IC<N - 1>{}); }
}

__device__ __forceinline__ void quad_origin(int win, int w, bool valid, int& row, int& col2) {
  col2 = (4 * (win & 63) + 2 + 2 * (w & 1)) & (IMG / 2 - 1);
  row = (8 * (win >> 6) + 4 + 4 * (w >> 1)) & (IMG - 1);
  if (!valid) row = IMG;
}
__device__ __forceinline__ void load_tile(uint32_t dst, int warp, int win, bool valid, uint32_t xbar, const CUtensorMap* tm_x) {
  int row, col2;
  quad_origin(win, warp, valid, row, col2);
  if (elect_one()) {
    mbar_expect_tx(xbar, 6144);
    tma_load5(dst, tm_x, row, col2, xbar);
  }
}
template <int S>
__device__ __forceinline__ void read_x(uint32_t (&xa)[48], const uint32_t (&xaddr)[4]) {
  ldmatrix_x4(xaddr[S & 3] + (S >> 2) * 2048, xa[4 * S], xa[4 * S + 1], xa[4 * S + 2], xa[4 * S + 3]);
}
__device__ __forceinline__ void reads_done(uint32_t last, uint32_t dummy_addr) {
  asm volatile("{\n.reg .pred p;\nsetp.eq.u32 p, %0, 0x7fc1fc17;\n@p st.shared.u32 [%1], %0;\n}\n" ::"r"(last), "r"(dummy_addr) : "memory");
}
template <int P>
__device__ __forceinline__ void store_chunk(uint32_t addr, float (&d)[48]) {
  stmatrix_x4(addr, pack_bf16(d[8 * P + 0], d[8 * P + 1]), pack_bf16(d[8 * P + 2], d[8 * P + 3]),
              pack_bf16(d[8 * P + 4], d[8 * P + 5]), pack_bf16(d[8 * P + 6], d[8 * P + 7]));
}
template <uint32_t WOFF, int H, bool TIED, class F>
__device__ __forceinline__ void gemm_phase(float (&run)[48], uint32_t (&x)[48], uint64_t w4, uint32_t rzero, F&& after) {
  wg_fence();
  static_for<12>([&](auto I) {
    constexpr int s = decltype(I)::v;
    const uint64_t d = desc_at<WOFF + (s / 6) * W_HALF + (s % 6) * 1024, 6144>(pin(w4));
    if constexpr (s == 0 && TIED) wgmma_n96_p(run, x[0], x[1], x[2], x[3], d, rzero);
    else if constexpr (s == 0) wgmma_n96_z(run, x[0], x[1], x[2], x[3], d);
    else wgmma_n96_a(run, x[4 * s], x[4 * s + 1], x[4 * s + 2], x[4 * s + 3], d);
    if constexpr (s == H - 1 || s == 11) wg_commit();
    if constexpr (s == H - 1) { after(IC<-100>{}); wg_wait<1>(); }
    after(I);
  });
}
template <int H>
__device__ __forceinline__ void issue_s(float (&s)[32], uint32_t (&q)[24], uint64_t k4_) {
  const uint64_t k4 = pin(k4_);
  static_for<3>([&](auto I) {
    constexpr int k = decltype(I)::v, i = 12 * H + 4 * k;
    const uint64_t d = desc_at<OFF_K + H * 768 + k * 256, 128>(k4);
    if constexpr (k == 0) wgmma_n64_z(s, q[i], q[i + 1], q[i + 2], q[i + 3], d);
    else wgmma_n64_a(s, q[i], q[i + 1], q[i + 2], q[i + 3], d);
  });
  wg_commit();
}
__device__ __forceinline__ const uint8_t* offset_ptr(const uint8_t* base, uint32_t off) {
  const uint8_t* r;
  asm volatile("{\n.reg .u64 o;\ncvt.u64.u32 o, %2;\nadd.u64 %0, %1, o;\n}\n" : "=l"(r) : "l"(base), "r"(off));
  return r;
}
struct MaskRows { uint4 a, b, c, d; };
__device__ __forceinline__ MaskRows mask_load(const uint8_t* mp) {
  MaskRows r;
  r.a = ldg128(mp); r.b = ldg128(mp + 1024); r.c = ldg128(mp + 2048); r.d = ldg128(mp + 3072);
  return r;
}
__device__ __forceinline__ void pin_rows(MaskRows& r) {
  asm volatile("" : "+r"(r.a.x), "+r"(r.a.y), "+r"(r.a.z), "+r"(r.a.w), "+r"(r.b.x), "+r"(r.b.y), "+r"(r.b.z), "+r"(r.b.w),
                    "+r"(r.c.x), "+r"(r.c.y), "+r"(r.c.z), "+r"(r.c.w), "+r"(r.d.x), "+r"(r.d.y), "+r"(r.d.z), "+r"(r.d.w)::"memory");
}
__device__ __forceinline__ uint32_t mask_or(const MaskRows& r) {
  return (r.a.x | r.a.y | r.a.z | r.a.w) | (r.b.x | r.b.y | r.b.z | r.b.w) | (r.c.x | r.c.y | r.c.z | r.c.w) | (r.d.x | r.d.y | r.d.z | r.d.w);
}
__device__ __forceinline__ void add_mask(float (&s0)[32], float (&s1)[32], const uint4 (&m)[4]) {
#pragma unroll
  for (int t = 0; t < 2; t++) {
#pragma unroll
    for (int b = 0; b < 8; b++) {
      const uint4 u = m[2 * t + (b >> 2)];
      const uint32_t v = (b & 3) == 0 ? u.x : (b & 3) == 1 ? u.y : (b & 3) == 2 ? u.z : u.w;
      const int i = 4 * b + 2 * t;
      s0[i] = fmaf(bf_lo(v), LOG2E, s0[i]); s0[i + 1] = fmaf(bf_hi(v), LOG2E, s0[i + 1]);
      s1[i] = fmaf(bf_lo(v), LOG2E, s1[i]); s1[i + 1] = fmaf(bf_hi(v), LOG2E, s1[i + 1]);
    }
  }
}
__device__ __forceinline__ void subtract_row_max(float (&s)[32]) {
#pragma unroll
  for (int t = 0; t < 2; t++) {
    float x = -INFINITY;
#pragma unroll
    for (int b = 0; b < 8; b++) x = fmaxf(x, fmaxf(s[4 * b + 2 * t], s[4 * b + 2 * t + 1]));
    x = fmaxf(x, __shfl_xor_sync(0xffffffffu, x, 1));
    x = fmaxf(x, __shfl_xor_sync(0xffffffffu, x, 2));
#pragma unroll
    for (int b = 0; b < 8; b++) { s[4 * b + 2 * t] -= x; s[4 * b + 2 * t + 1] -= x; }
  }
}
template <int I0, int I1>
__device__ __forceinline__ void exp_pairs(float (&s)[32]) {
#pragma unroll
  for (int i = 2 * I0; i < 2 * I1; i++) {
    asm volatile("" : "+f"(s[i])::"memory");
    s[i] = ex2(s[i]);
    asm volatile("" : "+f"(s[i])::"memory");
  }
}
template <int I0, int I1>
__device__ __forceinline__ void pack_pairs(float (&s)[32], const uint32_t (&eb)[16], uint32_t (&p)[16], uint32_t (&z)[6]) {
#pragma unroll
  for (int i = I0; i < I1; i++) {
    asm volatile("" : "+f"(s[2 * i]), "+f"(s[2 * i + 1])::"memory");
    p[i] = hmul2(pack_bf16(s[2 * i], s[2 * i + 1]), eb[i]);
    asm volatile("" : "+r"(p[i])::"memory");
    const int b = i >> 1, t = i & 1;
    if (!ONES && (b & 1)) {
      uint32_t v = hadd2(p[i - 2], p[i]);
      if (b & 2) v = hadd2(z[4 + t], v);
      if (b == 7) v = hadd2(z[2 + t], v);
      uint32_t& dst = z[(b == 7 ? 0 : (b & 2) ? 2 : 4) + t];
      dst = v;
      asm volatile("" : "+r"(dst)::"memory");
    }
  }
}
struct RowSums {
  uint32_t a, b, c, d;
  __device__ __forceinline__ void start(const uint32_t (&z)[6]) {
    a = hadd2(__byte_perm(z[0], z[1], 0x5410), __byte_perm(z[0], z[1], 0x7632));
    b = __shfl_xor_sync(0xffffffffu, a, 1);
    c = __shfl_xor_sync(0xffffffffu, a, 2);
    d = __shfl_xor_sync(0xffffffffu, a, 3);
  }
  __device__ __forceinline__ uint32_t finish() {
    asm volatile("" : "+r"(a), "+r"(b), "+r"(c), "+r"(d)::"memory");
    const uint32_t x = hadd2(a, b), y = hadd2(c, d);
    return pack_bf16(rcp_approx(bf_lo(x) + bf_lo(y)), rcp_approx(bf_hi(x) + bf_hi(y)));
  }
};
template <int H>
__device__ __forceinline__ void issue_pv(float (&oacc)[NO], uint32_t (&p)[16], uint64_t v4_) {
  const uint64_t v4 = pin(v4_);
  static_for<4>([&](auto I) {
    constexpr int k = decltype(I)::v;
    const uint64_t d = desc_at<OFF_V + H * 6144 + k * 256, 128>(v4);
    if constexpr (k == 0) wgmma_n48_z(oacc, p[0], p[1], p[2], p[3], d);
    else wgmma_n48_a(oacc, p[4 * k], p[4 * k + 1], p[4 * k + 2], p[4 * k + 3], d);
  });
  wg_commit();
}
template <int H, int K>
__device__ __forceinline__ void pv_step(float (&oacc)[NO], uint32_t (&p)[16], uint64_t v4) {
  const uint64_t d = desc_at<OFF_V + H * 6144 + K * 256, 128>(pin(v4));
  wg_fence();
  if constexpr (K == 0) wgmma_n48_z(oacc, p[0], p[1], p[2], p[3], d);
  else wgmma_n48_a(oacc, p[4 * K], p[4 * K + 1], p[4 * K + 2], p[4 * K + 3], d);
  if constexpr (K == 3) wg_commit();
}
constexpr uint32_t BAD_SUM = 0xE000E000u;
template <int H>
__device__ __forceinline__ uint32_t normalize(float (&oacc)[NO], uint32_t r, uint32_t (&o)[48]) {
  constexpr int c = ONES ? 4 * H : 0;
  if (ONES) r = pack_bf16(rcp_approx(oacc[H ? 0 : NO - 4]), rcp_approx(oacc[H ? 2 : NO - 2]));
  const uint32_t ra = dup_lo(r), rb = dup_hi(r);
#pragma unroll
  for (int k = 0; k < 12; k++) o[12 * H + k] = hmul2(pack_bf16(oacc[c + 2 * k], oacc[c + 2 * k + 1]), (k & 1) ? rb : ra);
  return r - 0x2F802F80u;
}

struct Params {
  const __nv_bfloat16 *x, *wqkv, *wo, *rpb;
  const int* rp_idx;
  const __nv_bfloat16* mask;
  __nv_bfloat16* out;
  int nk_min, nk_rem, wstride, wskip, zero;
};
__device__ __forceinline__ float round_bf16(float v) { return __bfloat162float(__float2bfloat16(v)); }
__device__ __forceinline__ void redo_window(const Params& P, float* sm, int win, int rank) {
  float* xt = sm;
  float* qkv = sm + 192 * 64;
  const int tid = threadIdx.x;
  auto pixel = [&](int n) { return (size_t)(((8 * (win >> 6) + (n >> 3) + 4) & (IMG - 1)) * IMG + ((8 * (win & 63) + (n & 7) + 4) & (IMG - 1))) * CH; };
  auto gemm = [&](const __nv_bfloat16* w, int ldw, int ncols, auto&& put) {
    for (int e = tid; e < 4 * ncols; e += THREADS) {
      const int g = e / ncols, d = e - g * ncols;
      float acc[16];
#pragma unroll
      for (int i = 0; i < 16; i++) acc[i] = 0.f;
      for (int c = 0; c < CH; c++) {
        const float wv = __bfloat162float(w[c * ldw + d]);
#pragma unroll
        for (int i = 0; i < 16; i++) acc[i] = fmaf(xt[c * 64 + 16 * g + i], wv, acc[i]);
      }
#pragma unroll
      for (int i = 0; i < 16; i++) put(16 * g + i, d, acc[i]);
    }
  };
  __syncthreads();
  for (int e = tid; e < 64 * CH; e += THREADS) xt[(e % CH) * 64 + e / CH] = __bfloat162float(P.x[pixel(e / CH) + e % CH]);
  __syncthreads();
  gemm(P.wqkv, 3 * CH, 3 * CH, [&](int n, int d, float v) { qkv[n * 577 + d] = round_bf16(v); });
  __syncthreads();
  {
    const int n = tid & 63, h = tid >> 6;
    auto logit = [&](int m) {
      float s = 0.f;
      for (int d = 0; d < 48; d++) s = fmaf(qkv[n * 577 + 48 * h + d], qkv[m * 577 + CH + 48 * h + d], s);
      return s * SCALE + __bfloat162float(P.rpb[P.rp_idx[n * 64 + m] * 4 + h]) + __bfloat162float(P.mask[(size_t)win * 4096 + n * 64 + m]);
    };
    float mx = -INFINITY, sum = 0.f, o[48];
    for (int m = 0; m < 64; m++) mx = fmaxf(mx, logit(m));
#pragma unroll
    for (int d = 0; d < 48; d++) o[d] = 0.f;
    for (int m = 0; m < 64; m++) {
      const float p = expf(logit(m) - mx);
      sum += p;
#pragma unroll
      for (int d = 0; d < 48; d++) o[d] = fmaf(p, qkv[m * 577 + 2 * CH + 48 * h + d], o[d]);
    }
#pragma unroll
    for (int d = 0; d < 48; d++) xt[(48 * h + d) * 64 + n] = round_bf16(o[d] / sum);
  }
  __syncthreads();
  gemm(P.wo + 96 * rank, CH, 96, [&](int n, int d, float v) { P.out[pixel(n) + 96 * rank + d] = __float2bfloat16(v); });
}

#define HD 6
#define HO HD
#define HQ HD
#define HV HD
#define E0 5
#define E1 10
#define ET 3
#define TOK 13
#define XSL "11110022220000"
#define XD 11
#define MS 8
#define PFP 22
#define KF 2
#define LF 9
#define SCHV force
#define QT 0
#define MSB 1
#define WPF 2
#define TPF 1
#define KW 0
#define X1P 2
#define OF -1
#define OF2 (E0 >= 12 ? 5 : -1)
#define M1E 0
#define SBM 0
#define TSB(i) do { if ((SBM >> (i)) & 1) sched(); TS(i); } while (0)
#define PFD 4
#define QP 0
#define VP 3
#define XP0 1
#define KP 1
#define KE 0
#define RA 0
#define RB 1
#define RC 0
#define RD 0
#define XW 1
#define MB 0
#define NB_T 0
#define NB_K 0
#define NB_V 0
#define PVI 0
#define PVS 1
#define SP 1
#define AO 0
#define EXP 1
#define FV 0
#define FVS -100
#define PRE 0
#define PF1 0
#define M0P 0
#define K1W 0
#define X2P 4
#define GP 0
#define NB 4
#define LAG 2
__host__ __device__ constexpr int g0(int r) { return r < 5 ? 3 * r : 16; }
__host__ __device__ constexpr int g1(int r) { return NB + (16 - NB) * r / 4; }
__host__ __device__ constexpr int xslot(int i) { return XSL[i] - '0'; }
__host__ __device__ constexpr int xbase(int i) { int b = 0; for (int q = 0; q < i; q++) b += xslot(q); return b; }
__host__ __device__ constexpr int xlast() { int l = 0; for (int q = 0; q < 14; q++) if (xslot(q)) l = q; return l; }
static_assert(!PVI || (NB == 2 && LAG == 2), "PVI");
static_assert(xbase(14) == 12 && XD >= xlast(), "X schedule");

__global__ void __cluster_dims__(2, 1, 1) __launch_bounds__(THREADS, 1)
swin_attn_kernel(const __grid_constant__ CUtensorMap tm_x, const __grid_constant__ CUtensorMap tm_o, const __grid_constant__ CUtensorMap tm_w,
                 const __grid_constant__ CUtensorMap tm_wo, const __grid_constant__ Params P) {
  extern __shared__ __align__(1024) uint8_t smem_raw[];
  const uint32_t sbase = smem_u32(smem_raw);
  const int tid = threadIdx.x;
  const int wid = uniform(tid >> 5);
  const int j = wid >> 2, warp = wid & 3;
  const uint32_t lane = tid & 31;
  uint32_t rank;
  asm("mov.u32 %0, %%cluster_ctarank;" : "=r"(rank));
  auto load_w = [&](int part) {
#pragma unroll
    for (int h = 0; h < 2; h++) {
      const uint32_t b = sbase + B_W + (part == 0 && h == 0 ? 32 : 8 * part);
      if (part == 0 || h == 0) mbar_expect_tx(b, part == 0 ? W_HALF : W_PART);
      if (part < 3) tma_load3(sbase + OFF_W + part * W_PART + h * W_HALF, &tm_w, 96 * h, (part == 0 ? 6 : part == 1 ? 0 : 12) + 3 * rank, b);
      else tma_load3(sbase + WO + h * W_HALF, &tm_wo, 96 * (rank ^ h), 3 * rank, b);
    }
  };
  uint32_t tab[4] = {0, 0, 0, 0};
  if ((wid >> 1) == 2) {
    const uint32_t* tp = reinterpret_cast<const uint32_t*>(P.rpb) + 2 * (tid - 128) + rank;
#pragma unroll
    for (int i = 0; i < 4; i++)
      if (i < 3 || tid < 128 + 33) asm volatile("ld.global.nc.u32 %0, [%1];" : "=r"(tab[i]) : "l"(tp + 128 * i) : "memory");
    if (elect_one()) {
      const uint32_t b = sbase + OFF_BAR + 128 * (wid & 1);
#pragma unroll
      for (uint32_t o = B_TOKEN; o <= B_LFREE; o += 8) mbar_init(b + o, 4);
      if (wid == 4) {
        mbar_arrive4(b + B_TOKEN);
        mbar_arrive4(b + B_KFREE);
        mbar_arrive4(b + B_VFREE);
      } else {
        mbar_init(sbase + B_DONE, 8);
      }
      asm volatile("fence.mbarrier_init.release.cluster;" ::: "memory");
    }
  } else {
    if (WPF && wid == 7 && lane < 18 && blockIdx.x < 128)
      asm volatile("prefetch.global.L2 [%0];" ::"l"((blockIdx.x < 96 ? reinterpret_cast<const uint8_t*>(P.wqkv) + blockIdx.x * 2304 : reinterpret_cast<const uint8_t*>(P.wo) + (blockIdx.x - 96) * 2304) + lane * 128) : "memory");
    if (elect_one()) {
      const uint32_t b0 = sbase + (j == 0 ? OFF_BAR + B_XFULL + 8 * warp : wid == 6 ? B_IDX : B_W);
      const uint32_t b1 = sbase + (j == 0 ? OFF_BAR + 128 + B_XFULL + 8 * warp : wid == 6 ? B_W + 8 : B_W + 32);
      const uint32_t b2 = sbase + (j == 0 ? OFF_BAR + 128 + B_X1 + 8 * warp : wid == 6 ? B_W + 16 : B_W + 24);
      mbar_init(b0, 1);
      mbar_init(b1, 1);
      mbar_init(b2, 1);
      if (j == 0) mbar_arrive(b1);
      fence_async_proxy();
      if (wid == 6) {
        mbar_expect_tx(sbase + B_IDX, 16384);
        bulk_load(sbase + WO, P.rp_idx, 16384, sbase + B_IDX);
      }
      if (KP == 0 && wid == 7) load_w(0);
    }
  }
  __syncwarp();
  const int cluster = blockIdx.x >> 1;
  const int nk = uniform(P.nk_min + (cluster < P.nk_rem) + (tid >> 10));
  const bool special = P.wskip != 0;
  const int nspecial = (!special || cluster < 4) ? 0 : cluster < 7 ? 3 : 2;
  const int wbase = !special ? cluster : cluster < 4 ? 63 * cluster : cluster < 7 ? 13 + 59 * cluster : 7 + 60 * cluster;
  auto window = [&](int k) { const int a = wbase + k * P.wstride; return a + (int)((uint32_t)(a * P.wskip) >> 20); };
  auto window_any = [&](int k) {
    const int v = k < 2 ? 2 * (cluster - 4) + k : 120 + cluster, w = window(k), b = v < 64 ? 4032 + v : 64 * (v - 64) + 63;
    return k >= nspecial ? w : b;
  };
  int win = window_any(j);
  const uint8_t* mask_b = reinterpret_cast<const uint8_t*>(P.mask);
  const uint32_t quad_row = 32 * (warp >> 1) + 4 * (warp & 1);
  const uint8_t* mask_q0 = mask_b + quad_row * 128;
  MaskRows mr;
  if (j == 0) {
    if (M0P == 0) mr = mask_load(mask_q0 + (size_t)win * 8192 + lane * 16);
    load_tile(sbase + OFF_X + warp * 6144, warp, win, true, sbase + OFF_BAR + B_XFULL + 8 * warp, &tm_x);
    if (M0P == 1) mr = mask_load(mask_q0 + (size_t)win * 8192 + lane * 16);
  }
  if (KP == 1 && wid == 7 && elect_one()) load_w(0);
  TS(24);
  if (sbase & 1023) __trap();
  const uint32_t bar = uniform(smem_u32(smem_raw) + OFF_BAR + (tid & 128)), bar_o = uniform(smem_u32(smem_raw) + OFF_BAR + ((tid & 128) ^ 128));
  const uint32_t xbar = uniform(smem_u32(smem_raw) + OFF_BAR + (tid & 128) + B_XFULL + 8 * ((tid >> 5) & 3));
  const uint32_t xbar_o = uniform(smem_u32(smem_raw) + OFF_BAR + ((tid & 128) ^ 128) + B_XFULL + 8 * ((tid >> 5) & 3));
  const uint32_t xdst = uniform(smem_u32(smem_raw) + OFF_X + ((tid >> 5) & 3) * 6144);
  const uint32_t x1off = j == 0 ? 0 : warp < 2 ? OFF_L + 12288 : WO + 16384 - 12288;
  auto loads = [&](int step) {
    if (j == 1) {
      if (QP == step && warp == 0 && elect_one()) load_w(1);
      if (X1P == step) load_tile(xdst + x1off, warp, win, true, xbar + B_X1, &tm_x);
      if (VP == step && warp == 2 && elect_one()) load_w(2);
      if (X2P == step) load_tile(xdst, warp, window_any(2), 2 < nk, xbar_o, &tm_x);
    }
  };
  asm volatile("st.shared.u32 [%0], %1;" ::"r"(sbase + OFF_FAIL + 4 * tid), "r"(0) : "memory");
  if (ONES) asm volatile("st.shared.u32 [%0], %1;" ::"r"(sbase + OFF_V + 6144 + 4 * tid), "r"(0x3F803F80u) : "memory");
  if (KP == 2 && wid == 7 && elect_one()) load_w(0);
  bool big = false;
  if ((wid >> 1) == 2) {
#pragma unroll
    for (int i = 0; i < 4; i++) {
      const float b0 = bf_lo(tab[i]) * LOG2E, b1 = bf_hi(tab[i]) * LOG2E;
      asm volatile("st.shared.u32 [%0], %1;" ::"r"(sbase + OFF_TAB + 4 * (tid - 128) + 256 * i), "r"(pack_bf16(ex2(b0), ex2(b1))) : "memory");
      big = big || !(fabsf(b0) <= 60.f && fabsf(b1) <= 60.f);
    }
  }
  if (M1E && j == 1) mr = mask_load(mask_q0 + (size_t)win * 8192 + lane * 16);
  TS(25);
  uint32_t force = __syncthreads_or(big) ? BAD_SUM : 0u;
  asm volatile("barrier.cluster.arrive.relaxed.aligned;" ::: "memory");
  TS(26);
  if (KP == 3 && wid == 7 && elect_one()) load_w(0);
  loads(0);
  TS(27);
  const uint32_t sb_a = uniform((sbase & 0x3FFFF) >> 4);
  const uint64_t w4 = desc_base<512, 2>(sb_a), k4 = desc_base<UB>(sb_a), v4 = desc_base<1024>(sb_a);
  const uint32_t blk = 2 * warp + ((lane >> 3) & 1);
  uint32_t stk = sbase + OFF_K + blk * UB + (lane >> 4) * 128 + (lane & 7) * 16;
  uint32_t stv = sbase + OFF_V + (lane >> 4) * 1024 + blk * 128 + (lane & 7) * 16;
  uint32_t xaddr0 = xdst + (lane & 15) * 128 + (((lane >> 4) ^ (lane & 7)) << 4);
  const uint32_t peer = rank ^ 1;
  const uint32_t area = uniform(smem_u32(smem_raw) + OFF_L + (tid >> 5) * 3072);
  const uint32_t r_bar = uniform(mapa(bar, peer)), r_area = uniform(mapa(area, peer));
  uint32_t l16 = lane * 16;
  uint32_t out_res = area + (lane & 15) * 64 + (((lane >> 4) ^ ((lane >> 1) & 3)) << 4);
  const uint32_t rzero = uniform(P.zero + (tid >> 10));
  const uint64_t mq = reinterpret_cast<uint64_t>(mask_b) + (32 * ((tid >> 6) & 1) + 4 * ((tid >> 5) & 1)) * 128;
  const uint8_t* mask_q = reinterpret_cast<const uint8_t*>(((uint64_t)uniform((uint32_t)(mq >> 32)) << 32) | uniform((uint32_t)mq));

  sched_barrier(stk, rzero); sched_barrier(stv, rzero); sched_barrier(xaddr0, rzero); sched_barrier(out_res, rzero); sched_barrier(l16, rzero);
  uint32_t xa[48], oo[48], eb0[16], eb1[16];
  auto fetch = [&](auto H) {
    constexpr int o = 24 + 12 * decltype(H)::v;
    const uint32_t addr = area + l16 + 1536 * decltype(H)::v;
    const uint4 x = lds128v(addr), y = lds128v(addr + 512), z = lds128v(addr + 1024);
    oo[o + 0] = x.x; oo[o + 1] = x.y; oo[o + 2] = x.z; oo[o + 3] = x.w; oo[o + 4] = y.x; oo[o + 5] = y.y; oo[o + 6] = y.z; oo[o + 7] = y.w;
    oo[o + 8] = z.x; oo[o + 9] = z.y; oo[o + 10] = z.z; oo[o + 11] = z.w;
  };
  auto store_out = [&](auto PP, float (&d)[48]) {
    constexpr int p = decltype(PP)::v;
    store_chunk<p>(((p & 1) ? (out_res ^ 32) : out_res) + (p >> 1) * 1024, d);
  };
  auto send_out = [&](int w, bool valid) {
    int row, col2;
    quad_origin(w, warp, valid, row, col2);
    if (elect_one()) tma_store5(&tm_o, row, col2, 3 * rank, area);
    asm volatile("cp.async.bulk.commit_group;" ::: "memory");
  };
  auto prefetch_mask = [&](int w) {
    if (elect_one()) prefetch_l2(mask_b + (size_t)w * 8192 + (rank * 4 + warp) * 1024, 1024);
  };
  auto prefetch_x = [&](int w) {
    if ((warp >> 1) == rank) {
      int row, col2;
      quad_origin(w, warp, true, row, col2);
      if (elect_one()) tma_prefetch5(&tm_x, row, col2);
    }
  };

  auto first_x = [&]() {
    uint32_t xaddr[4], all = ~0u;
#pragma unroll
    for (int q = 0; q < 4; q++) xaddr[q] = (xaddr0 + x1off) ^ (q << 5);
    mbar_wait(xbar + j * B_X1, 0);
    TS(29);
    static_for<12>([&](auto I) { read_x<decltype(I)::v>(xa, xaddr); all &= xa[4 * decltype(I)::v + 3]; });
    reads_done(all, sbase + OFF_DUMMY);
    TS(30);
  };
  auto gather = [&]() {
    const uint32_t odd = (l16 >> 6) & 1;
    const uint32_t ia = sbase + WO + (quad_row + 8 * (l16 >> 7) + odd) * 256 + (l16 & 0x30) * 2;
    mbar_wait(sbase + B_IDX, 0);
#pragma unroll
    for (int i = 0; i < 4; i++) {
      const int t = i >> 1, b = 4 * (i & 1);
      const uint4 u0 = lds128(ia + t * 512 + (i & 1) * 128 + odd * 16), u1 = lds128(ia + t * 512 + (i & 1) * 128 + 16 - odd * 16);
      const uint32_t id[8] = {u0.x, u0.y, u0.z, u0.w, u1.x, u1.y, u1.z, u1.w};
      uint32_t v[8];
#pragma unroll
      for (int q = 0; q < 8; q++) v[q] = lds32(sbase + OFF_TAB + 4 * id[q]);
#pragma unroll
      for (int q = 0; q < 4; q++) {
        const uint32_t x = odd ? v[(2 * q) ^ 4] : v[2 * q], y = odd ? v[(2 * q + 1) ^ 4] : v[2 * q + 1];
        eb0[2 * (b + q) + t] = __byte_perm(x, y, 0x5410);
        eb1[2 * (b + q) + t] = __byte_perm(x, y, 0x7632);
      }
    }
    TS(31);
  };
  gather();
#pragma unroll
  for (int i = 0; i < 16; i += 4) {
    asm volatile("{\n.reg .pred p;\nsetp.ne.u32 p, %4, 0;\n@p ld.shared.v4.u32 {%0,%1,%2,%3}, [%4];\n}\n" : "+r"(eb0[i]), "+r"(eb0[i + 1]), "+r"(eb0[i + 2]), "+r"(eb0[i + 3]) : "r"(rzero));
    asm volatile("{\n.reg .pred p;\nsetp.ne.u32 p, %4, 0;\n@p ld.shared.v4.u32 {%0,%1,%2,%3}, [%4];\n}\n" : "+r"(eb1[i]), "+r"(eb1[i + 1]), "+r"(eb1[i + 2]), "+r"(eb1[i + 3]) : "r"(rzero));
  }
  loads(1);
  if (j == 0) first_x();
  TS(28);
#pragma unroll
  for (int h = 0; h < 2; h++) {
    constexpr uint32_t HI = 0x3E553E55u, LO = 0x396E396Eu;
    const uint32_t a = sbase + WK + h * 16384 + tid * 16;
    uint4 v[5];
    if (h == 0) mbar_wait(sbase + B_W + 32, 0);
    else mbar_wait(sbase + B_W, 0);
    TS(32 + h);
#pragma unroll
    for (int i = 0; i < 4 + h; i++) v[i] = lds128(a + i * 4096);
    loads(2 + h);
#pragma unroll
    for (int i = 0; i < 4 + h; i++)
      sts128(a + i * 4096, make_uint4(hfma2(v[i].x, HI, hmul2(v[i].x, LO)), hfma2(v[i].y, HI, hmul2(v[i].y, LO)),
                                      hfma2(v[i].z, HI, hmul2(v[i].z, LO)), hfma2(v[i].w, HI, hmul2(v[i].w, LO))));
  }
  fence_async_proxy();
  TS(21);
  bool shifted = false;
  if (j == 0) {
    pin_rows(mr);
    shifted = __any_sync(0xffffffffu, mask_or(mr) != 0);
  }
  __syncthreads();
  TS(22);
  if (j == 1) {
    loads(4);
    if (!M1E) mr = mask_load(mask_q0 + (size_t)win * 8192 + lane * 16);
    first_x();
    loads(5);
    wg_barrier(1);
    if (warp == 3 && elect_one()) load_w(3);
    if (2 < nk) prefetch_mask(window_any(2));
    if (3 < nk) {
      prefetch_x(window(3));
      prefetch_mask(window(3));
    }
    pin_rows(mr);
    shifted = __any_sync(0xffffffffu, mask_or(mr) != 0);
    if (NB_V) hand_over(N_VFREE);
  }

  uint32_t par = 0;
  auto sched = [&]() { sched_barrier(SCHV, rzero); };
  int k = j, wprev = win, wnext = window_any(j + 2);
#pragma unroll
  for (int i = 0; i < 24; i++) oo[i] = 0;
  TS(23);
  for (;;) {
    float ca[48], cb[48], s0[32], s1[32];
    uint32_t qf[24];
    const int wnn = window(k + 4);
    auto prefetches = [&]() {
      if (k + 4 < nk) {
        prefetch_mask(wnn);
        prefetch_x(wnn);
      }
    };
    auto expect = [&]() {
      if (l16 == 0) {
        mbar_expect_tx(bar + B_EX0, 1536);
        mbar_expect_tx(bar + B_EX1, 1536);
      }
    };
    int xrow, xcol;
    const uint8_t* mnext;
    bool ex0, ex1, kfree = true;
    auto pass = [&](uint32_t b, int id, bool named) {
      if (named) hand_over(id + (j ^ 1));
      else if (l16 == 0) mbar_arrive(bar_o + b);
    };
    TSB(1);
    fence_regs(xa);
    auto ex_step = [&](auto G) {
      constexpr int g = decltype(G)::v;
      if constexpr (g == E0 - ET) ex0 = mbar_test(bar + B_EX0, par ^ 1);
      if constexpr (g == (E1 == 50 ? 12 + HO - 1 : E1) - ET) ex1 = mbar_test(bar + B_EX1, par ^ 1);
      if constexpr (g == E0) { if (!ex0) mbar_wait(bar + B_EX0, par ^ 1); fetch(IC<0>{}); }
      if constexpr (g == E1) { if (!ex1) mbar_wait(bar + B_EX1, par ^ 1); fetch(IC<1>{}); }
    };
    gemm_phase<WK, 0, false>(cb, xa, w4, rzero, [&](auto I) { ex_step(I); TSS(24 + decltype(I)::v); });
    TSB(2);
    if (!AO && k == j) {
      cluster_wait();
      if (NB_T && j == 1) take_over(N_TOKEN + 1);
      if (!NB_K) mbar_wait(bar + B_KFREE, 0);
      else if (j == 1) take_over(N_KFREE + 1);
      wg_wait<0>();
      TS(34);
      fence_regs(cb);
      static_for<6>([&](auto PP) { store_chunk<decltype(PP)::v>(stk + decltype(PP)::v * 256, cb); });
      wg_fence();
      wgmma_n96_z(ca, xa[0], xa[1], xa[2], xa[3], desc_at<WK, 6144>(pin(w4)));
      wg_commit();
      mbar_wait(sbase + B_W + 8, 0);
      TS(35);
    } else {
      gemm_phase<WO, HO, false>(ca, oo, w4, rzero, [&](auto I) {
        constexpr int s = decltype(I)::v, p = s - (HO - 1);
        if constexpr (p == -2 && !NB_K) kfree = mbar_test(bar + B_KFREE, par);
        if constexpr (p == 0) { fence_regs(cb); TSB(3); if (NB_K) take_over(N_KFREE + j); else if (!kfree) mbar_wait(bar + B_KFREE, par); }
        if constexpr (p >= 0 && p < 6) store_chunk<(p >= 0 && p < 6) ? p : 0>(stk + p * 256, cb);
        if constexpr (s == -100 && PFP == 20) prefetches();
        if constexpr (s == -100) ex_step(IC<50>{});
        ex_step(IC<12 + s>{});
        if constexpr (s == OF || s == OF2) wg_fence();
        if constexpr (s >= 0) TSS(36 + s);
      });
    }
    if (AO && k == j) {
      cluster_wait();
      mbar_wait(sbase + B_W + 8, 0);
    }
    gemm_phase<WQ, HQ, false>(cb, xa, w4, rzero, [&](auto I) {
      constexpr int s = decltype(I)::v, p = s - (HQ - 1);
      if constexpr (s == -100 && PFP == 21) prefetches();
      if constexpr (p == 0) { fence_regs(ca); TSB(4); }
      if constexpr (p >= 0 && p < 6) store_out(IC<(p >= 0 && p < 6) ? p : 0>{}, ca);
      if constexpr (s >= 0) TSS(48 + s);
    });
    if (k == j) {
      TS(36);
      mbar_wait(sbase + B_W + 16, 0);
      TS(37);
      if (j == 1) mbar_wait(sbase + B_W + 24, 0);
    }
    gemm_phase<WV, HV, true>(ca, xa, w4, rzero, [&](auto I) {
      constexpr int s = decltype(I)::v, p = s - (HV - 1);
      if constexpr (s == -100 && PFP == 22) { if (!PF1 || k != j) prefetches(); }
      if constexpr (s == -100 && EXP == 1) expect();
      if constexpr (s == -100 && PRE) {
        quad_origin(window(k + 3), warp, k + 3 < nk, xrow, xcol);
        mnext = mask_q + (size_t)(k + 2 < nk ? wnext : win) * 8192;
        asm volatile("" : "+r"(xrow), "+r"(xcol), "+l"(mnext)::"memory");
        if (PRE == 2) sched();
      }
      if constexpr (s == FVS && FV >= 1) {
        fence_async_proxy();
        if (FV == 2) { __syncwarp(); send_out(wprev, k != j); }
      }
      if constexpr (p == 0) { fence_regs(cb); TSB(6); }
      if constexpr (p >= 0 && p < 6) {
#pragma unroll
        for (int i = 4 * p; i < 4 * p + 4; i++) {
          if (i >= QT) { qf[i] = pack_bf16(cb[2 * i], cb[2 * i + 1]); continue; }
          qf[i] = oo[24 + i];
          asm("{\n.reg .pred p;\nsetp.eq.u32 p, %3, 0;\n@p cvt.rn.bf16x2.f32 %0, %1, %2;\n}\n" : "+r"(qf[i]) : "f"(cb[2 * i + 1]), "f"(cb[2 * i]), "r"(rzero));
        }
      }
      if constexpr (s == TOK) pass(B_TOKEN, N_TOKEN, NB_T);
      if constexpr (s >= 0) TSS(60 + s);
    });
    fence_regs(qf);
    if (FV == 0) fence_async_proxy();
    TSB(5);
    wg_barrier(j);
    const bool vfree = NB_V || mbar_test(bar + B_VFREE, par), xfull = mbar_test(xbar, par ^ 1);
    wg_fence();
    issue_s<0>(s0, qf, k4);
    if (TOK == 12) pass(B_TOKEN, N_TOKEN, NB_T);
    issue_s<1>(s1, qf, k4);
    if (TOK == 13) pass(B_TOKEN, N_TOKEN, NB_T);
    TSB(7);
    if (FV < 2) send_out(wprev, k != j);
    if (EXP == 0) expect();
    uint32_t xaddr[4];
#pragma unroll
    for (int q = 0; q < 4; q++) xaddr[q] = xaddr0 ^ (q << 5);
    auto side = [&](auto R) {
      constexpr int r = decltype(R)::v, c = xslot(r), b = xbase(r);
      if constexpr (r == KF) {
        wg_wait<0>();
        fence_regs(s1);
        fence_regs(qf);
        pass(B_KFREE, N_KFREE, NB_K);
      }
      if constexpr (r == LF) {
        asm volatile("cp.async.bulk.wait_group.read 0;" ::: "memory");
        __syncwarp();
        if (l16 == 0) mbar_arrive_remote_relaxed(r_bar + B_LFREE);
      }
      if constexpr (XW == 1 && b == 0 && c > 0) { if (!xfull) mbar_wait(xbar, par ^ 1); TSB(19); }
      if constexpr (r == MS) {
        if (!PRE) mnext = mask_q + (size_t)(k + 2 < nk ? wnext : win) * 8192;
        mr = mask_load(offset_ptr(mnext, l16));
        if (MB) sched();
      }
      static_for<c>([&](auto J) { read_x<b + decltype(J)::v>(xa, xaddr); });
      if constexpr (r == XD) {
        uint32_t all = ~0u;
#pragma unroll
        for (int i = 12 - xslot(xlast()); i < 12; i++) all &= xa[4 * i + 3];
        reads_done(all, sbase + OFF_DUMMY);
        if (!PRE) quad_origin(window(k + 3), warp, k + 3 < nk, xrow, xcol);
        if (elect_one()) {
          mbar_expect_tx(xbar_o, 6144);
          tma_load5(xdst, &tm_x, xrow, xcol, xbar_o);
        }
        TSB(15);
      }
      if constexpr (r == PFP) prefetches();
      if constexpr (PF1 && r == PF1) { if (k == j) prefetches(); }
    };
    auto store_v = [&](auto PP) {
      constexpr int p = decltype(PP)::v;
      store_chunk<p>(stv + p * 2048 + (ONES && p >= 3 ? 1024 : 0), ca);
    };
    float o0[NO], o1[NO];
    uint32_t p0[16], p1[16], z0[6], z1[6], r0 = 0, r1 = 0;
    RowSums l0, l1;
    if (NB_V) take_over(N_VFREE + j);
    if (!vfree) mbar_wait(bar + B_VFREE, par);
    if (XW == 0 && !xfull) mbar_wait(xbar, par ^ 1);
    auto shift = [&]() {
    if (shifted) {
      uint32_t l = l16;
      asm volatile("" : "+r"(l));
      const uint8_t* mp = offset_ptr(mask_q + (size_t)win * 8192, (l & 0x180) * 8 + (l & 0x40) * 2 + (l & 0x30));
      wg_wait<0>();
      if (SP == 0) fence_regs(xa);
      fence_regs(s0);
      fence_regs(s1);
      const uint4 m[4] = {ldg128(mp), ldg128(mp + 64), ldg128(mp + 256), ldg128(mp + 320)};
      add_mask(s0, s1, m);
      if (__any_sync(0xffffffffu, force != 0)) {
        subtract_row_max(s0);
        subtract_row_max(s1);
      }
    }
    };
    if (SP == 0) shift();
    wg_wait<2>();
    fence_regs(ca);
    fence_regs(xa);
    TSB(8);
    store_v(IC<0>{});
    side(IC<0>{});
    store_v(IC<1>{});
    wg_wait<1>();
    fence_regs(s0);
    TSB(9);
    static_for<5>([&](auto R) {
      constexpr int r = decltype(R)::v;
      side(IC<1 + r>{});
      if constexpr (r == 0 && SP == 1) shift();
      if constexpr (r < 4) store_v(IC<(r < 4 ? r + 2 : 0)>{});
      exp_pairs<g0(r), g0(r + 1)>(s0);
      pack_pairs<(g0(r) > LAG ? g0(r) - LAG : 0), g0(r + 1) - LAG>(s0, eb0, p0, z0);
      sched();
    });
    TSB(10);
    fence_async_proxy();
    exp_pairs<0, NB>(s1);
    pack_pairs<16 - LAG, 16>(s0, eb0, p0, z0);
    pack_pairs<0, (NB > LAG ? NB - LAG : 0)>(s1, eb1, p1, z1);
    if (!ONES && RC == 0) l0.start(z0);
    sched();
    wg_barrier(j);
    if (!ONES && RC == 1) { l0.start(z0); if (RD) sched(); }
    side(IC<6>{});
    if (PVI) {
      static_for<7>([&](auto M) {
        constexpr int m = decltype(M)::v;
        if constexpr (m < 4) pv_step<0, (m < 4 ? m : 0)>(o0, p0, v4);
        else pv_step<1, (m >= 4 ? m - 4 : 0)>(o1, p1, v4);
        sched();
        if constexpr (m == 0) TSB(11);
        if constexpr (!ONES && m == 2 * RA) r0 = l0.finish();
        if constexpr ((m & 1) == 0) side(IC<7 + m / 2>{});
        exp_pairs<2 + 2 * m, 4 + 2 * m>(s1);
        pack_pairs<2 * m, (m < 6 ? 2 * m + 2 : 16)>(s1, eb1, p1, z1);
        if (m < 6 && PVS) sched();
      });
      TSB(12);
      if (!ONES && RB == 0) l1.start(z1);
      pv_step<1, 3>(o1, p1, v4);
      sched();
    } else {
    wg_fence();
    issue_pv<0>(o0, p0, v4);
    sched();
    TSB(11);
    static_for<4>([&](auto R) {
      constexpr int r = decltype(R)::v;
      if constexpr (!ONES && r == RA) r0 = l0.finish();
      side(IC<7 + r>{});
      exp_pairs<g1(r), g1(r + 1)>(s1);
      pack_pairs<(g1(r) > LAG ? g1(r) - LAG : 0), (r < 3 ? g1(r + 1) - LAG : 16)>(s1, eb1, p1, z1);
      if (r < 3) sched();
    });
    TSB(12);
    if (MS == 14) { sched(); mr = mask_load(offset_ptr(mask_q + (size_t)(k + 2 < nk ? wnext : win) * 8192, l16)); }
    if (!ONES && RB == 0) l1.start(z1);
    wg_fence();
    issue_pv<1>(o1, p1, v4);
    sched();
    }
    if (!ONES && RB == 1) l1.start(z1);
    side(IC<11>{});
    wg_wait<1>();
    fence_regs(o0);
    fence_regs(p0);
    TSB(13);
    uint32_t bad = normalize<0>(o0, r0, oo);
    mbar_wait(bar + B_LFREE, par);
#pragma unroll
    for (int q = 0; q < 3; q++) st_async16(r_area + l16 + q * 512, oo[4 * q], oo[4 * q + 1], oo[4 * q + 2], oo[4 * q + 3], r_bar + B_EX0);
    TSB(14);
    if (!ONES && RB == 1) sched();
    if (!ONES) r1 = l1.finish();
    side(IC<12>{});
    wg_wait<0>();
    fence_regs(o1);
    fence_regs(p1);
    TSB(16);
    pass(B_VFREE, N_VFREE, NB_V);
    bad = ((bad | normalize<1>(o1, r1, oo)) & BAD_SUM) | force;
#pragma unroll
    for (int q = 3; q < 6; q++) st_async16(r_area + l16 + q * 512, oo[4 * q], oo[4 * q + 1], oo[4 * q + 2], oo[4 * q + 3], r_bar + B_EX1);
    if (MSB) sched();
    TSB(17);
    side(IC<13>{});
    pin_rows(mr);
    shifted = __any_sync(0xffffffffu, (mask_or(mr) | bad) != 0);
    if (shifted && __any_sync(0xffffffffu, (bad & BAD_SUM) != 0)) {
      force |= 1;
      if ((l16 >> 4) == (uint32_t)(k >> 6)) asm volatile("red.shared.or.b32 [%0], %1;" ::"r"(sbase + OFF_FAIL + 512 * j + 128 * warp + (l16 >> 2)), "r"(1u << ((k >> 1) & 31)) : "memory");
    }
    wprev = win;
    win = wnext;
    wnext = wnn;
    k += 2;
    if (k >= nk) break;
    par ^= 1;
    TSB(18);
    TS_SET(k);
    TSB(0);
    if (NB_T) take_over(N_TOKEN + j); else mbar_wait(bar + B_TOKEN, par);
  }
  {
    const uint32_t a = sbase + OFF_FAIL + 512 * j + 128 * warp + (l16 >> 2);
    asm volatile("st.async.weak.shared::cluster.mbarrier::complete_tx::bytes.b32 [%0], %1, [%2];" ::"r"(mapa(a + 1024, peer)), "r"(lds32(a)), "r"(mapa(sbase + B_DONE, peer)) : "memory");
    __syncwarp();
    if (l16 == 0) mbar_expect_tx(sbase + B_DONE, 128);
  }
  {
    float ca[48];
    mbar_wait(sbase + B_W + 24, 0);
    gemm_phase<WO, 0, false>(ca, oo, w4, rzero, [&](auto I) {
      constexpr int s = decltype(I)::v;
      if constexpr (s == 5) { mbar_wait(bar + B_EX0, par); fetch(IC<0>{}); wg_fence(); }
      if constexpr (s == 8) { mbar_wait(bar + B_EX1, par); fetch(IC<1>{}); wg_fence(); }
    });
    wg_wait<0>();
    fence_regs(ca);
    fence_regs(oo);
    static_for<6>([&](auto PP) { store_out(PP, ca); });
    fence_async_proxy();
    __syncwarp();
    send_out(wprev, true);
  }
  TS(21);
  if (k == nk + 1) mbar_wait(xbar_o, j ? par : par ^ 1);
  mbar_wait(sbase + B_DONE, 0);
  uint32_t failed = 0;
#pragma unroll
  for (int i = 0; i < 4; i++) {
    const uint4 f = lds128(sbase + OFF_FAIL + 512 * i + l16);
    failed |= f.x | f.y | f.z | f.w;
  }
  if (__any_sync(0xffffffffu, failed != 0)) {
    asm volatile("cp.async.bulk.wait_group 0;" ::: "memory");
    asm volatile("fence.proxy.async;" ::: "memory");
    for (int kk = 0; kk < nk; kk++) {
      uint32_t f = 0;
      for (int i = 0; i < 8; i++) f |= lds32(sbase + OFF_FAIL + 1024 * (i >> 2) + 512 * (kk & 1) + 128 * (i & 3) + 4 * (kk >> 6));
      if ((f >> ((kk >> 1) & 31)) & 1) redo_window(P, reinterpret_cast<float*>(smem_raw), window_any(kk), rank);
    }
  }
  asm volatile("cp.async.bulk.wait_group.read 0;" ::: "memory");
  TS(22);
}

typedef CUresult (*EncodeTiledFn)(CUtensorMap*, CUtensorMapDataType, cuuint32_t, void*, const cuuint64_t*, const cuuint64_t*,
                                  const cuuint32_t*, const cuuint32_t*, CUtensorMapInterleave, CUtensorMapSwizzle,
                                  CUtensorMapL2promotion, CUtensorMapFloatOOBfill);

void encode_image_map(EncodeTiledFn fn, CUtensorMap* tm, void* ptr, uint32_t group_c, CUtensorMapSwizzle sw) {
  const cuuint64_t dims[5] = {(cuuint64_t)group_c, 2, (cuuint64_t)IMG, (cuuint64_t)IMG / 2, (cuuint64_t)(CH / group_c)};
  const cuuint64_t strides[4] = {(cuuint64_t)CH * 2, (cuuint64_t)CH * 2 * IMG, (cuuint64_t)CH * 4, (cuuint64_t)group_c * 2};
  const cuuint32_t box[5] = {group_c, 2, 4, 2, 3};
  const cuuint32_t estr[5] = {1, 1, 1, 1, 1};
  fn(tm, CU_TENSOR_MAP_DATA_TYPE_BFLOAT16, 5, ptr, dims, strides, box, estr, CU_TENSOR_MAP_INTERLEAVE_NONE, sw,
     CU_TENSOR_MAP_L2_PROMOTION_L2_128B, CU_TENSOR_MAP_FLOAT_OOB_FILL_NONE);
}
void encode_weight_map(EncodeTiledFn fn, CUtensorMap* tm, void* ptr, uint32_t cols) {
  const cuuint64_t dims[3] = {32, (cuuint64_t)CH, (cuuint64_t)(cols / 32)};
  const cuuint64_t strides[2] = {(cuuint64_t)cols * 2, 64};
  const cuuint32_t box[3] = {32, 96, 3};
  const cuuint32_t estr[3] = {1, 1, 1};
  fn(tm, CU_TENSOR_MAP_DATA_TYPE_BFLOAT16, 3, ptr, dims, strides, box, estr, CU_TENSOR_MAP_INTERLEAVE_NONE, CU_TENSOR_MAP_SWIZZLE_64B,
     CU_TENSOR_MAP_L2_PROMOTION_L2_128B, CU_TENSOR_MAP_FLOAT_OOB_FILL_NONE);
}

}

extern "C" void kernel_launch(void* const* d_in, const int* in_sizes, int n_in, void* d_out, int out_size) {
  (void)in_sizes; (void)n_in; (void)out_size;
  static int nclusters = 0;
  static EncodeTiledFn encode = nullptr;
  if (nclusters == 0) {
    cudaFuncSetAttribute(swin_attn_kernel, cudaFuncAttributeMaxDynamicSharedMemorySize, SMEM_BYTES);
    int dev = 0, sms = 0;
    cudaGetDevice(&dev);
    cudaDeviceGetAttribute(&sms, cudaDevAttrMultiProcessorCount, dev);
    nclusters = sms / 2;
    cudaLaunchConfig_t cfg = {};
    cfg.gridDim = dim3(2 * nclusters);
    cfg.blockDim = dim3(THREADS);
    cfg.dynamicSmemBytes = SMEM_BYTES;
    cudaLaunchAttribute at[1];
    at[0].id = cudaLaunchAttributeClusterDimension;
    at[0].val.clusterDim.x = 2; at[0].val.clusterDim.y = 1; at[0].val.clusterDim.z = 1;
    cfg.attrs = at; cfg.numAttrs = 1;
    int maxc = 0;
    if (cudaOccupancyMaxActiveClusters(&maxc, swin_attn_kernel, &cfg) == cudaSuccess && maxc > 0 && maxc < nclusters) nclusters = maxc;
    (void)cudaGetLastError();
    void* fn = nullptr;
    cudaDriverEntryPointQueryResult qres;
    cudaGetDriverEntryPoint("cuTensorMapEncodeTiled", &fn, cudaEnableDefault, &qres);
    encode = (EncodeTiledFn)fn;
  }
  CUtensorMap tm_x, tm_o, tm_w, tm_wo;
  encode_image_map(encode, &tm_x, d_in[0], 64, CU_TENSOR_MAP_SWIZZLE_128B);
  encode_image_map(encode, &tm_o, d_out, 32, CU_TENSOR_MAP_SWIZZLE_64B);
  encode_weight_map(encode, &tm_w, d_in[1], 3 * CH);
  encode_weight_map(encode, &tm_wo, d_in[2], CH);
  Params P;
  P.x = (const __nv_bfloat16*)d_in[0];
  P.wqkv = (const __nv_bfloat16*)d_in[1];
  P.wo = (const __nv_bfloat16*)d_in[2];
  P.rpb = (const __nv_bfloat16*)d_in[3];
  P.rp_idx = (const int*)d_in[4];
  P.mask = (const __nv_bfloat16*)d_in[5];
  P.out = (__nv_bfloat16*)d_out;
  P.wstride = nclusters == 66 ? 1 : nclusters;
  P.wskip = nclusters == 66 ? 16645 : 0;
  P.zero = 0;
  P.nk_min = NWIN / nclusters;
  P.nk_rem = NWIN % nclusters;
  swin_attn_kernel<<<2 * nclusters, THREADS, SMEM_BYTES, cudaStreamPerThread>>>(tm_x, tm_o, tm_w, tm_wo, P);
}
```

```cpp
#include <cuda_runtime.h>
#include <cuda_bf16.h>
#include <cuda.h>
#include <stdint.h>

namespace {

constexpr int IMG = 512, CH = 192, NWIN = 4096;
constexpr int THREADS = 256;

constexpr uint32_t OFF_X = 0;
constexpr uint32_t OFF_K = 24576;
constexpr uint32_t UB = 1536;
constexpr uint32_t OFF_V = OFF_K + 12288;
constexpr uint32_t OFF_L = OFF_V + 12288;
constexpr uint32_t OFF_W = OFF_L + 2 * 12288;
constexpr uint32_t W_HALF = 3 * 96 * 64, W_PART = 2 * W_HALF;
constexpr uint32_t WK = OFF_W, WQ = OFF_W + W_PART, WV = OFF_W + 2 * W_PART, WO = OFF_W + 3 * W_PART;
constexpr uint32_t OFF_BAR = OFF_W + 4 * W_PART;
constexpr uint32_t B_XFULL = 0;
constexpr uint32_t B_TOKEN = 32;
constexpr uint32_t B_KFREE = 40, B_VFREE = 48;
constexpr uint32_t B_EX0 = 56, B_EX1 = 64;
constexpr uint32_t B_LFREE = 72;
constexpr uint32_t B_X1 = 80;
constexpr uint32_t B_W = OFF_BAR + 256;
constexpr uint32_t B_IDX = OFF_BAR + 296;
constexpr uint32_t B_DONE = OFF_BAR + 304;
constexpr uint32_t OFF_DUMMY = OFF_BAR + 320;
constexpr uint32_t OFF_FAIL = OFF_BAR + 384;
constexpr uint32_t OFF_TAB = OFF_FAIL + 2048;
constexpr uint32_t OFF_TS = OFF_TAB + 1024;
constexpr uint32_t SMEM_BYTES = OFF_TS;

constexpr float LOG2E = 1.4426950408889634f;
constexpr float SCALE = 0.14433756729740643f;

__device__ __forceinline__ uint32_t smem_u32(const void* p) { return (uint32_t)__cvta_generic_to_shared(p); }
__device__ __forceinline__ void wg_fence() { asm volatile("wgmma.fence.sync.aligned;" ::: "memory"); }
__device__ __forceinline__ void wg_commit() { asm volatile("wgmma.commit_group.sync.aligned;" ::: "memory"); }
template <int N> __device__ __forceinline__ void wg_wait() { asm volatile("wgmma.wait_group.sync.aligned %0;" ::"n"(N) : "memory"); }
template <int N> __device__ __forceinline__ void fence_regs(float (&d)[N]) {
#pragma unroll
  for (int i = 0; i < N; i++) asm volatile("" : "+f"(d[i])::"memory");
}
template <int N> __device__ __forceinline__ void fence_regs(uint32_t (&d)[N]) {
#pragma unroll
  for (int i = 0; i < N; i++) asm volatile("" : "+r"(d[i])::"memory");
}
__device__ __forceinline__ bool elect_one() {
  uint32_t pred;
  asm volatile("{\n.reg .pred p;\nelect.sync _|p, 0xffffffff;\nselp.u32 %0, 1, 0, p;\n}\n" : "=r"(pred));
  return pred != 0;
}
__device__ __forceinline__ uint32_t pack_bf16(float lo, float hi) {
  uint32_t r;
  asm("cvt.rn.bf16x2.f32 %0, %1, %2;" : "=r"(r) : "f"(hi), "f"(lo));
  return r;
}
__device__ __forceinline__ float bf_lo(uint32_t v) { return __uint_as_float(v << 16); }
__device__ __forceinline__ float bf_hi(uint32_t v) { return __uint_as_float(v & 0xffff0000u); }
__device__ __forceinline__ float ex2(float x) {
  float y;
  asm("ex2.approx.ftz.f32 %0, %1;" : "=f"(y) : "f"(x));
  return y;
}
__device__ __forceinline__ uint32_t hadd2(uint32_t a, uint32_t b) {
  uint32_t r;
  asm("add.rn.bf16x2 %0, %1, %2;" : "=r"(r) : "r"(a), "r"(b));
  return r;
}
__device__ __forceinline__ uint32_t hmul2(uint32_t a, uint32_t b) {
  uint32_t r;
  asm("mul.rn.bf16x2 %0, %1, %2;" : "=r"(r) : "r"(a), "r"(b));
  return r;
}
__device__ __forceinline__ uint32_t dup_lo(uint32_t a) {
  uint32_t r;
  asm("{\n.reg .b16 l, h;\nmov.b32 {l, h}, %1;\nmov.b32 %0, {l, l};\n}\n" : "=r"(r) : "r"(a));
  return r;
}
__device__ __forceinline__ uint32_t dup_hi(uint32_t a) {
  uint32_t r;
  asm("{\n.reg .b16 l, h;\nmov.b32 {l, h}, %1;\nmov.b32 %0, {h, h};\n}\n" : "=r"(r) : "r"(a));
  return r;
}
__device__ __forceinline__ float rcp_approx(float x) {
  float y;
  asm("rcp.approx.ftz.f32 %0, %1;" : "=f"(y) : "f"(x));
  return y;
}
__device__ __forceinline__ uint4 ldg128(const void* p) {
  uint4 v;
  asm volatile("ld.global.L1::evict_normal.v4.u32 {%0,%1,%2,%3}, [%4];" : "=r"(v.x), "=r"(v.y), "=r"(v.z), "=r"(v.w) : "l"(p) : "memory");
  return v;
}
__device__ __forceinline__ void prefetch_l2(const void* p, uint32_t bytes) {
  asm volatile("cp.async.bulk.prefetch.L2.global [%0], %1;" ::"l"(p), "r"(bytes) : "memory");
}
__device__ __forceinline__ uint4 lds128(uint32_t addr) {
  uint4 v;
  asm volatile("ld.shared.v4.u32 {%0,%1,%2,%3}, [%4];" : "=r"(v.x), "=r"(v.y), "=r"(v.z), "=r"(v.w) : "r"(addr) : "memory");
  return v;
}
__device__ __forceinline__ uint4 lds128v(uint32_t addr) {
  uint4 v;
  asm volatile("ld.volatile.shared.v4.u32 {%0,%1,%2,%3}, [%4];" : "=r"(v.x), "=r"(v.y), "=r"(v.z), "=r"(v.w) : "r"(addr) : "memory");
  return v;
}
__device__ __forceinline__ uint32_t lds32(uint32_t addr) {
  uint32_t v;
  asm volatile("ld.shared.u32 %0, [%1];" : "=r"(v) : "r"(addr) : "memory");
  return v;
}
__device__ __forceinline__ void stmatrix_x4(uint32_t addr, uint32_t a, uint32_t b, uint32_t c, uint32_t d) {
  asm volatile("stmatrix.sync.aligned.m8n8.x4.shared.b16 [%0], {%1,%2,%3,%4};" ::"r"(addr), "r"(a), "r"(b), "r"(c), "r"(d) : "memory");
}
__device__ __forceinline__ void ldmatrix_x4(uint32_t addr, uint32_t& a, uint32_t& b, uint32_t& c, uint32_t& d) {
  asm volatile("ldmatrix.sync.aligned.m8n8.x4.shared.b16 {%0,%1,%2,%3}, [%4];" : "=r"(a), "=r"(b), "=r"(c), "=r"(d) : "r"(addr) : "memory");
}
__device__ __forceinline__ void fence_async_proxy() {
  asm volatile("fence.proxy.async.shared::cta;" ::: "memory");
}
__device__ __forceinline__ void wg_barrier(int j) { asm volatile("bar.sync %0, 128;" ::"r"(1 + j) : "memory"); }
__device__ __forceinline__ void cluster_wait() { asm volatile("barrier.cluster.wait.acquire.aligned;" ::: "memory"); }
__device__ __forceinline__ uint32_t mapa(uint32_t a, uint32_t rank) {
  uint32_t o;
  asm("mapa.shared::cluster.u32 %0, %1, %2;" : "=r"(o) : "r"(a), "r"(rank));
  return o;
}
__device__ __forceinline__ void mbar_init(uint32_t a, uint32_t cnt) { asm volatile("mbarrier.init.shared::cta.b64 [%0], %1;" ::"r"(a), "r"(cnt) : "memory"); }
__device__ __forceinline__ void mbar_expect_tx(uint32_t a, uint32_t tx) {
  asm volatile("mbarrier.arrive.expect_tx.shared::cta.b64 _, [%0], %1;" ::"r"(a), "r"(tx) : "memory");
}
__device__ __forceinline__ void mbar_arrive(uint32_t a) { asm volatile("mbarrier.arrive.shared::cta.b64 _, [%0];" ::"r"(a) : "memory"); }
__device__ __forceinline__ void mbar_arrive4(uint32_t a) { asm volatile("mbarrier.arrive.shared::cta.b64 _, [%0], 4;" ::"r"(a) : "memory"); }
__device__ __forceinline__ uint32_t uniform(uint32_t v) { return __shfl_sync(0xffffffffu, v, 0); }
__device__ __forceinline__ void mbar_arrive_remote_relaxed(uint32_t a) {
  asm volatile("mbarrier.arrive.relaxed.cluster.shared::cluster.b64 _, [%0];" ::"r"(a) : "memory");
}
__device__ __forceinline__ void mbar_wait(uint32_t a, uint32_t parity) {
  asm volatile(
      "{\n.reg .pred p;\n.reg .u32 n;\n"
      "mbarrier.try_wait.parity.shared::cta.b64 p, [%0], %1;\n"
      "@p bra WAIT_DONE;\n"
      "mov.u32 n, 0;\n"
      "WAIT_LOOP:\n"
      "add.u32 n, n, 1;\n"
      "setp.gt.u32 p, n, 4000000;\n"
      "@p trap;\n"
      "mbarrier.try_wait.parity.shared::cta.b64 p, [%0], %1;\n"
      "@!p bra WAIT_LOOP;\n"
      "WAIT_DONE:\n}\n" ::"r"(a), "r"(parity) : "memory");
}
__device__ __forceinline__ bool mbar_test(uint32_t a, uint32_t parity) {
  uint32_t ok;
  asm volatile("{\n.reg .pred p;\nmbarrier.test_wait.parity.shared::cta.b64 p, [%1], %2;\nselp.u32 %0, 1, 0, p;\n}\n" : "=r"(ok) : "r"(a), "r"(parity) : "memory");
  return ok != 0;
}
__device__ __forceinline__ uint32_t hfma2(uint32_t a, uint32_t b, uint32_t c) {
  uint32_t r;
  asm("fma.rn.bf16x2 %0, %1, %2, %3;" : "=r"(r) : "r"(a), "r"(b), "r"(c));
  return r;
}
__device__ __forceinline__ void st_async16(uint32_t raddr, uint32_t a, uint32_t b, uint32_t c, uint32_t d, uint32_t rbar) {
  asm volatile("st.async.weak.shared::cluster.mbarrier::complete_tx::bytes.v4.b32 [%0], {%1,%2,%3,%4}, [%5];" ::"r"(raddr),
               "r"(a), "r"(b), "r"(c), "r"(d), "r"(rbar) : "memory");
}

__device__ __forceinline__ void st_async4(uint32_t raddr, uint32_t v, uint32_t rbar) {
  asm volatile("st.async.weak.shared::cluster.mbarrier::complete_tx::bytes.b32 [%0], %1, [%2];" ::"r"(raddr), "r"(v), "r"(rbar) : "memory");
}
__device__ __forceinline__ void sts128(uint32_t addr, uint4 v) {
  asm volatile("st.shared.v4.u32 [%0], {%1,%2,%3,%4};" ::"r"(addr), "r"(v.x), "r"(v.y), "r"(v.z), "r"(v.w) : "memory");
}
__device__ __forceinline__ void bulk_load(uint32_t dst, const void* src, uint32_t bytes, uint32_t bar) {
  asm volatile("cp.async.bulk.shared::cta.global.mbarrier::complete_tx::bytes [%0], [%1], %2, [%3];" ::"r"(dst), "l"(src),
               "r"(bytes), "r"(bar) : "memory");
}
__device__ __forceinline__ void tma_load3(uint32_t dst, const CUtensorMap* tm, int c1, int c2, uint32_t bar) {
  asm volatile("cp.async.bulk.tensor.3d.shared::cta.global.tile.mbarrier::complete_tx::bytes [%0], [%1, {0, %2, %3}], [%4];" ::"r"(dst),
               "l"(tm), "r"(c1), "r"(c2), "r"(bar) : "memory");
}
__device__ __forceinline__ void tma_load5(uint32_t dst, const CUtensorMap* tm, int c2, int c3, uint32_t bar) {
  asm volatile("cp.async.bulk.tensor.5d.shared::cta.global.tile.mbarrier::complete_tx::bytes [%0], [%1, {0, 0, %2, %3, 0}], [%4];" ::"r"(dst),
               "l"(tm), "r"(c2), "r"(c3), "r"(bar) : "memory");
}
__device__ __forceinline__ void tma_prefetch5(const CUtensorMap* tm, int c2, int c3) {
  asm volatile("cp.async.bulk.prefetch.tensor.5d.L2.global.tile [%0, {0, 0, %1, %2, 0}];" ::"l"(tm), "r"(c2), "r"(c3) : "memory");
}
__device__ __forceinline__ void tma_store5(const CUtensorMap* tm, int c2, int c3, int c4, uint32_t src) {
  asm volatile("cp.async.bulk.tensor.5d.global.shared::cta.tile.bulk_group [%0, {0, 0, %1, %2, %3}], [%4];" ::"l"(tm), "r"(c2), "r"(c3),
               "r"(c4), "r"(src) : "memory");
}
__device__ __forceinline__ void sched_barrier(uint32_t& t, uint32_t zero) {
  asm volatile("{\n.reg .pred p;\nsetp.ne.u32 p, %1, 0;\n@p mov.u32 %0, %%clock;\n}\n" : "+r"(t) : "r"(zero) : "memory");
}

#define TS(i)
#define TS_SET(k)
#define TSS(i)
__device__ __forceinline__ void wgmma_n48_a(float (&d)[24], uint32_t a0, uint32_t a1, uint32_t a2, uint32_t a3, uint64_t db) {
  asm volatile("{\n.reg .pred p;\nsetp.ne.b32 p, 1, 0;\n"
      "wgmma.mma_async.sync.aligned.m64n48k16.f32.bf16.bf16 "
      "{%0,%1,%2,%3,%4,%5,%6,%7,%8,%9,%10,%11,%12,%13,%14,%15,"
      "%16,%17,%18,%19,%20,%21,%22,%23}, "
      "{%24,%25,%26,%27}, %28, p, 1, 1, 1;\n}\n"
      : "+f"(d[0]), "+f"(d[1]), "+f"(d[2]), "+f"(d[3]), "+f"(d[4]), "+f"(d[5]), "+f"(d[6]), "+f"(d[7]),
        "+f"(d[8]), "+f"(d[9]), "+f"(d[10]), "+f"(d[11]), "+f"(d[12]), "+f"(d[13]), "+f"(d[14]), "+f"(d[15]),
        "+f"(d[16]), "+f"(d[17]), "+f"(d[18]), "+f"(d[19]), "+f"(d[20]), "+f"(d[21]), "+f"(d[22]), "+f"(d[23])
      : "r"(a0), "r"(a1), "r"(a2), "r"(a3), "l"(db));
}
__device__ __forceinline__ void wgmma_n48_z(float (&d)[24], uint32_t a0, uint32_t a1, uint32_t a2, uint32_t a3, uint64_t db) {
  asm volatile("{\n.reg .pred p;\nsetp.ne.b32 p, 0, 0;\n"
      "wgmma.mma_async.sync.aligned.m64n48k16.f32.bf16.bf16 "
      "{%0,%1,%2,%3,%4,%5,%6,%7,%8,%9,%10,%11,%12,%13,%14,%15,"
      "%16,%17,%18,%19,%20,%21,%22,%23}, "
      "{%24,%25,%26,%27}, %28, p, 1, 1, 1;\n}\n"
      : "=f"(d[0]), "=f"(d[1]), "=f"(d[2]), "=f"(d[3]), "=f"(d[4]), "=f"(d[5]), "=f"(d[6]), "=f"(d[7]),
        "=f"(d[8]), "=f"(d[9]), "=f"(d[10]), "=f"(d[11]), "=f"(d[12]), "=f"(d[13]), "=f"(d[14]), "=f"(d[15]),
        "=f"(d[16]), "=f"(d[17]), "=f"(d[18]), "=f"(d[19]), "=f"(d[20]), "=f"(d[21]), "=f"(d[22]), "=f"(d[23])
      : "r"(a0), "r"(a1), "r"(a2), "r"(a3), "l"(db));
}
__device__ __forceinline__ void wgmma_n96_a(float (&d)[48], uint32_t a0, uint32_t a1, uint32_t a2, uint32_t a3, uint64_t db) {
  asm volatile("{\n.reg .pred p;\nsetp.ne.b32 p, 1, 0;\n"
      "wgmma.mma_async.sync.aligned.m64n96k16.f32.bf16.bf16 "
      "{%0,%1,%2,%3,%4,%5,%6,%7,%8,%9,%10,%11,%12,%13,%14,%15,"
      "%16,%17,%18,%19,%20,%21,%22,%23,%24,%25,%26,%27,%28,%29,%30,%31,"
      "%32,%33,%34,%35,%36,%37,%38,%39,%40,%41,%42,%43,%44,%45,%46,%47}, "
      "{%48,%49,%50,%51}, %52, p, 1, 1, 1;\n}\n"
      : "+f"(d[0]), "+f"(d[1]), "+f"(d[2]), "+f"(d[3]), "+f"(d[4]), "+f"(d[5]), "+f"(d[6]), "+f"(d[7]),
        "+f"(d[8]), "+f"(d[9]), "+f"(d[10]), "+f"(d[11]), "+f"(d[12]), "+f"(d[13]), "+f"(d[14]), "+f"(d[15]),
        "+f"(d[16]), "+f"(d[17]), "+f"(d[18]), "+f"(d[19]), "+f"(d[20]), "+f"(d[21]), "+f"(d[22]), "+f"(d[23]),
        "+f"(d[24]), "+f"(d[25]), "+f"(d[26]), "+f"(d[27]), "+f"(d[28]), "+f"(d[29]), "+f"(d[30]), "+f"(d[31]),
        "+f"(d[32]), "+f"(d[33]), "+f"(d[34]), "+f"(d[35]), "+f"(d[36]), "+f"(d[37]), "+f"(d[38]), "+f"(d[39]),
        "+f"(d[40]), "+f"(d[41]), "+f"(d[42]), "+f"(d[43]), "+f"(d[44]), "+f"(d[45]), "+f"(d[46]), "+f"(d[47])
      : "r"(a0), "r"(a1), "r"(a2), "r"(a3), "l"(db));
}
__device__ __forceinline__ void wgmma_n96_z(float (&d)[48], uint32_t a0, uint32_t a1, uint32_t a2, uint32_t a3, uint64_t db) {
  asm volatile("{\n.reg .pred p;\nsetp.ne.b32 p, 0, 0;\n"
      "wgmma.mma_async.sync.aligned.m64n96k16.f32.bf16.bf16 "
      "{%0,%1,%2,%3,%4,%5,%6,%7,%8,%9,%10,%11,%12,%13,%14,%15,"
      "%16,%17,%18,%19,%20,%21,%22,%23,%24,%25,%26,%27,%28,%29,%30,%31,"
      "%32,%33,%34,%35,%36,%37,%38,%39,%40,%41,%42,%43,%44,%45,%46,%47}, "
      "{%48,%49,%50,%51}, %52, p, 1, 1, 1;\n}\n"
      : "=f"(d[0]), "=f"(d[1]), "=f"(d[2]), "=f"(d[3]), "=f"(d[4]), "=f"(d[5]), "=f"(d[6]), "=f"(d[7]),
        "=f"(d[8]), "=f"(d[9]), "=f"(d[10]), "=f"(d[11]), "=f"(d[12]), "=f"(d[13]), "=f"(d[14]), "=f"(d[15]),
        "=f"(d[16]), "=f"(d[17]), "=f"(d[18]), "=f"(d[19]), "=f"(d[20]), "=f"(d[21]), "=f"(d[22]), "=f"(d[23]),
        "=f"(d[24]), "=f"(d[25]), "=f"(d[26]), "=f"(d[27]), "=f"(d[28]), "=f"(d[29]), "=f"(d[30]), "=f"(d[31]),
        "=f"(d[32]), "=f"(d[33]), "=f"(d[34]), "=f"(d[35]), "=f"(d[36]), "=f"(d[37]), "=f"(d[38]), "=f"(d[39]),
        "=f"(d[40]), "=f"(d[41]), "=f"(d[42]), "=f"(d[43]), "=f"(d[44]), "=f"(d[45]), "=f"(d[46]), "=f"(d[47])
      : "r"(a0), "r"(a1), "r"(a2), "r"(a3), "l"(db));
}
__device__ __forceinline__ void wgmma_n96_p(float (&d)[48], uint32_t a0, uint32_t a1, uint32_t a2, uint32_t a3, uint64_t db, uint32_t acc) {
  asm volatile("{\n.reg .pred p;\nsetp.ne.b32 p, %53, 0;\n"
      "wgmma.mma_async.sync.aligned.m64n96k16.f32.bf16.bf16 "
      "{%0,%1,%2,%3,%4,%5,%6,%7,%8,%9,%10,%11,%12,%13,%14,%15,"
      "%16,%17,%18,%19,%20,%21,%22,%23,%24,%25,%26,%27,%28,%29,%30,%31,"
      "%32,%33,%34,%35,%36,%37,%38,%39,%40,%41,%42,%43,%44,%45,%46,%47}, "
      "{%48,%49,%50,%51}, %52, p, 1, 1, 1;\n}\n"
      : "+f"(d[0]), "+f"(d[1]), "+f"(d[2]), "+f"(d[3]), "+f"(d[4]), "+f"(d[5]), "+f"(d[6]), "+f"(d[7]),
        "+f"(d[8]), "+f"(d[9]), "+f"(d[10]), "+f"(d[11]), "+f"(d[12]), "+f"(d[13]), "+f"(d[14]), "+f"(d[15]),
        "+f"(d[16]), "+f"(d[17]), "+f"(d[18]), "+f"(d[19]), "+f"(d[20]), "+f"(d[21]), "+f"(d[22]), "+f"(d[23]),
        "+f"(d[24]), "+f"(d[25]), "+f"(d[26]), "+f"(d[27]), "+f"(d[28]), "+f"(d[29]), "+f"(d[30]), "+f"(d[31]),
        "+f"(d[32]), "+f"(d[33]), "+f"(d[34]), "+f"(d[35]), "+f"(d[36]), "+f"(d[37]), "+f"(d[38]), "+f"(d[39]),
        "+f"(d[40]), "+f"(d[41]), "+f"(d[42]), "+f"(d[43]), "+f"(d[44]), "+f"(d[45]), "+f"(d[46]), "+f"(d[47])
      : "r"(a0), "r"(a1), "r"(a2), "r"(a3), "l"(db), "r"(acc));
}
__device__ __forceinline__ void wgmma_n64_a(float (&d)[32], uint32_t a0, uint32_t a1, uint32_t a2, uint32_t a3, uint64_t db) {
  asm volatile("{\n.reg .pred p;\nsetp.ne.b32 p, 1, 0;\n"
      "wgmma.mma_async.sync.aligned.m64n64k16.f32.bf16.bf16 "
      "{%0,%1,%2,%3,%4,%5,%6,%7,%8,%9,%10,%11,%12,%13,%14,%15,"
      "%16,%17,%18,%19,%20,%21,%22,%23,%24,%25,%26,%27,%28,%29,%30,%31}, "
      "{%32,%33,%34,%35}, %36, p, 1, 1, 0;\n}\n"
      : "+f"(d[0]), "+f"(d[1]), "+f"(d[2]), "+f"(d[3]), "+f"(d[4]), "+f"(d[5]), "+f"(d[6]), "+f"(d[7]),
        "+f"(d[8]), "+f"(d[9]), "+f"(d[10]), "+f"(d[11]), "+f"(d[12]), "+f"(d[13]), "+f"(d[14]), "+f"(d[15]),
        "+f"(d[16]), "+f"(d[17]), "+f"(d[18]), "+f"(d[19]), "+f"(d[20]), "+f"(d[21]), "+f"(d[22]), "+f"(d[23]),
        "+f"(d[24]), "+f"(d[25]), "+f"(d[26]), "+f"(d[27]), "+f"(d[28]), "+f"(d[29]), "+f"(d[30]), "+f"(d[31])
      : "r"(a0), "r"(a1), "r"(a2), "r"(a3), "l"(db));
}
__device__ __forceinline__ void wgmma_n64_z(float (&d)[32], uint32_t a0, uint32_t a1, uint32_t a2, uint32_t a3, uint64_t db) {
  asm volatile("{\n.reg .pred p;\nsetp.ne.b32 p, 0, 0;\n"
      "wgmma.mma_async.sync.aligned.m64n64k16.f32.bf16.bf16 "
      "{%0,%1,%2,%3,%4,%5,%6,%7,%8,%9,%10,%11,%12,%13,%14,%15,"
      "%16,%17,%18,%19,%20,%21,%22,%23,%24,%25,%26,%27,%28,%29,%30,%31}, "
      "{%32,%33,%34,%35}, %36, p, 1, 1, 0;\n}\n"
      : "=f"(d[0]), "=f"(d[1]), "=f"(d[2]), "=f"(d[3]), "=f"(d[4]), "=f"(d[5]), "=f"(d[6]), "=f"(d[7]),
        "=f"(d[8]), "=f"(d[9]), "=f"(d[10]), "=f"(d[11]), "=f"(d[12]), "=f"(d[13]), "=f"(d[14]), "=f"(d[15]),
        "=f"(d[16]), "=f"(d[17]), "=f"(d[18]), "=f"(d[19]), "=f"(d[20]), "=f"(d[21]), "=f"(d[22]), "=f"(d[23]),
        "=f"(d[24]), "=f"(d[25]), "=f"(d[26]), "=f"(d[27]), "=f"(d[28]), "=f"(d[29]), "=f"(d[30]), "=f"(d[31])
      : "r"(a0), "r"(a1), "r"(a2), "r"(a3), "l"(db));
}

template <uint32_t OFF, uint32_t LBO>
__device__ __forceinline__ uint64_t desc_at(uint64_t base) {
  return base + (uint64_t)((OFF >> 4) + ((LBO >> 4) << 16));
}
template <uint32_t SBO, uint32_t SWIZZLE = 0>
__device__ __forceinline__ uint64_t desc_base(uint32_t addr4) {
  return ((uint64_t)SWIZZLE << 62) | ((uint64_t)(SBO >> 4) << 32) | (uint64_t)addr4;
}
__device__ __forceinline__ uint64_t pin(uint64_t v) {
  asm volatile("" : "+l"(v));
  return v;
}
template <int I> struct IC { static constexpr int v = I; };
template <int N, class F> __device__ __forceinline__ void static_for(F&& f) {
  if constexpr (N > 0) { static_for<N - 1>(f); f(IC<N - 1>{}); }
}

__device__ __forceinline__ void quad_origin(int win, int w, bool valid, int& row, int& col2) {
  col2 = (4 * (win & 63) + 2 + 2 * (w & 1)) & (IMG / 2 - 1);
  row = (8 * (win >> 6) + 4 + 4 * (w >> 1)) & (IMG - 1);
  if (!valid) row = IMG;
}
__device__ __forceinline__ void load_tile(uint32_t dst, int warp, int win, bool valid, uint32_t xbar, const CUtensorMap* tm_x) {
  int row, col2;
  quad_origin(win, warp, valid, row, col2);
  if (elect_one()) {
    mbar_expect_tx(xbar, 6144);
    tma_load5(dst, tm_x, row, col2, xbar);
  }
}
template <int S>
__device__ __forceinline__ void read_x(uint32_t (&xa)[48], const uint32_t (&xaddr)[4]) {
  ldmatrix_x4(xaddr[S & 3] + (S >> 2) * 2048, xa[4 * S], xa[4 * S + 1], xa[4 * S + 2], xa[4 * S + 3]);
}
__device__ __forceinline__ void reads_done(uint32_t last, uint32_t dummy_addr) {
  asm volatile("{\n.reg .pred p;\nsetp.eq.u32 p, %0, 0x7fc1fc17;\n@p st.shared.u32 [%1], %0;\n}\n" ::"r"(last), "r"(dummy_addr) : "memory");
}
template <int P>
__device__ __forceinline__ void store_chunk(uint32_t addr, float (&d)[48]) {
  stmatrix_x4(addr, pack_bf16(d[8 * P + 0], d[8 * P + 1]), pack_bf16(d[8 * P + 2], d[8 * P + 3]),
              pack_bf16(d[8 * P + 4], d[8 * P + 5]), pack_bf16(d[8 * P + 6], d[8 * P + 7]));
}
constexpr int IDLE = -100;
template <uint32_t WOFF, int H, bool TIED, class F>
__device__ __forceinline__ void gemm_phase(float (&run)[48], uint32_t (&x)[48], uint64_t w4, uint32_t rzero, F&& after) {
  wg_fence();
  static_for<12>([&](auto I) {
    constexpr int s = decltype(I)::v;
    const uint64_t d = desc_at<WOFF + (s / 6) * W_HALF + (s % 6) * 1024, 6144>(pin(w4));
    if constexpr (s == 0 && TIED) wgmma_n96_p(run, x[0], x[1], x[2], x[3], d, rzero);
    else if constexpr (s == 0) wgmma_n96_z(run, x[0], x[1], x[2], x[3], d);
    else wgmma_n96_a(run, x[4 * s], x[4 * s + 1], x[4 * s + 2], x[4 * s + 3], d);
    if constexpr (s == H - 1 || s == 11) wg_commit();
    if constexpr (s == H - 1) { after(IC<IDLE>{}); wg_wait<1>(); }
    after(I);
  });
}
template <int H>
__device__ __forceinline__ void issue_s(float (&s)[32], uint32_t (&q)[24], uint64_t k4_) {
  const uint64_t k4 = pin(k4_);
  static_for<3>([&](auto I) {
    constexpr int k = decltype(I)::v, i = 12 * H + 4 * k;
    const uint64_t d = desc_at<OFF_K + H * 768 + k * 256, 128>(k4);
    if constexpr (k == 0) wgmma_n64_z(s, q[i], q[i + 1], q[i + 2], q[i + 3], d);
    else wgmma_n64_a(s, q[i], q[i + 1], q[i + 2], q[i + 3], d);
  });
  wg_commit();
}
__device__ __forceinline__ const uint8_t* offset_ptr(const uint8_t* base, uint32_t off) {
  const uint8_t* r;
  asm volatile("{\n.reg .u64 o;\ncvt.u64.u32 o, %2;\nadd.u64 %0, %1, o;\n}\n" : "=l"(r) : "l"(base), "r"(off));
  return r;
}
struct MaskRows { uint4 a, b, c, d; };
__device__ __forceinline__ MaskRows mask_load(const uint8_t* mp) {
  MaskRows r;
  r.a = ldg128(mp); r.b = ldg128(mp + 1024); r.c = ldg128(mp + 2048); r.d = ldg128(mp + 3072);
  return r;
}
__device__ __forceinline__ void pin_rows(MaskRows& r) {
  asm volatile("" : "+r"(r.a.x), "+r"(r.a.y), "+r"(r.a.z), "+r"(r.a.w), "+r"(r.b.x), "+r"(r.b.y), "+r"(r.b.z), "+r"(r.b.w),
                    "+r"(r.c.x), "+r"(r.c.y), "+r"(r.c.z), "+r"(r.c.w), "+r"(r.d.x), "+r"(r.d.y), "+r"(r.d.z), "+r"(r.d.w)::"memory");
}
__device__ __forceinline__ uint32_t mask_or(const MaskRows& r) {
  return (r.a.x | r.a.y | r.a.z | r.a.w) | (r.b.x | r.b.y | r.b.z | r.b.w) | (r.c.x | r.c.y | r.c.z | r.c.w) | (r.d.x | r.d.y | r.d.z | r.d.w);
}
__device__ __forceinline__ void add_mask(float (&s0)[32], float (&s1)[32], const uint4 (&m)[4]) {
#pragma unroll
  for (int t = 0; t < 2; t++) {
#pragma unroll
    for (int b = 0; b < 8; b++) {
      const uint4 u = m[2 * t + (b >> 2)];
      const uint32_t v = (b & 3) == 0 ? u.x : (b & 3) == 1 ? u.y : (b & 3) == 2 ? u.z : u.w;
      const int i = 4 * b + 2 * t;
      s0[i] = fmaf(bf_lo(v), LOG2E, s0[i]); s0[i + 1] = fmaf(bf_hi(v), LOG2E, s0[i + 1]);
      s1[i] = fmaf(bf_lo(v), LOG2E, s1[i]); s1[i + 1] = fmaf(bf_hi(v), LOG2E, s1[i + 1]);
    }
  }
}
__device__ __forceinline__ void subtract_row_max(float (&s)[32]) {
#pragma unroll
  for (int t = 0; t < 2; t++) {
    float x = -INFINITY;
#pragma unroll
    for (int b = 0; b < 8; b++) x = fmaxf(x, fmaxf(s[4 * b + 2 * t], s[4 * b + 2 * t + 1]));
    x = fmaxf(x, __shfl_xor_sync(0xffffffffu, x, 1));
    x = fmaxf(x, __shfl_xor_sync(0xffffffffu, x, 2));
#pragma unroll
    for (int b = 0; b < 8; b++) { s[4 * b + 2 * t] -= x; s[4 * b + 2 * t + 1] -= x; }
  }
}
template <int I0, int I1>
__device__ __forceinline__ void exp_pairs(float (&s)[32]) {
#pragma unroll
  for (int i = 2 * I0; i < 2 * I1; i++) {
    asm volatile("" : "+f"(s[i])::"memory");
    s[i] = ex2(s[i]);
    asm volatile("" : "+f"(s[i])::"memory");
  }
}
template <int I0, int I1>
__device__ __forceinline__ void pack_pairs(float (&s)[32], const uint32_t (&eb)[16], uint32_t (&p)[16], uint32_t (&z)[6]) {
#pragma unroll
  for (int i = I0; i < I1; i++) {
    asm volatile("" : "+f"(s[2 * i]), "+f"(s[2 * i + 1])::"memory");
    p[i] = hmul2(pack_bf16(s[2 * i], s[2 * i + 1]), eb[i]);
    asm volatile("" : "+r"(p[i])::"memory");
    const int b = i >> 1, t = i & 1;
    if (b & 1) {
      uint32_t v = hadd2(p[i - 2], p[i]);
      if (b & 2) v = hadd2(z[4 + t], v);
      if (b == 7) v = hadd2(z[2 + t], v);
      uint32_t& dst = z[(b == 7 ? 0 : (b & 2) ? 2 : 4) + t];
      dst = v;
      asm volatile("" : "+r"(dst)::"memory");
    }
  }
}
struct RowSums {
  uint32_t a, b, c, d;
  __device__ __forceinline__ void start(const uint32_t (&z)[6]) {
    a = hadd2(__byte_perm(z[0], z[1], 0x5410), __byte_perm(z[0], z[1], 0x7632));
    b = __shfl_xor_sync(0xffffffffu, a, 1);
    c = __shfl_xor_sync(0xffffffffu, a, 2);
    d = __shfl_xor_sync(0xffffffffu, a, 3);
  }
  __device__ __forceinline__ uint32_t finish() {
    asm volatile("" : "+r"(a), "+r"(b), "+r"(c), "+r"(d)::"memory");
    const uint32_t x = hadd2(a, b), y = hadd2(c, d);
    return pack_bf16(rcp_approx(bf_lo(x) + bf_lo(y)), rcp_approx(bf_hi(x) + bf_hi(y)));
  }
};
template <int H>
__device__ __forceinline__ void issue_pv(float (&oacc)[24], uint32_t (&p)[16], uint64_t v4_) {
  const uint64_t v4 = pin(v4_);
  static_for<4>([&](auto I) {
    constexpr int k = decltype(I)::v;
    const uint64_t d = desc_at<OFF_V + H * 6144 + k * 256, 128>(v4);
    if constexpr (k == 0) wgmma_n48_z(oacc, p[0], p[1], p[2], p[3], d);
    else wgmma_n48_a(oacc, p[4 * k], p[4 * k + 1], p[4 * k + 2], p[4 * k + 3], d);
  });
  wg_commit();
}
constexpr uint32_t BAD_SUM = 0xE000E000u;
template <int H>
__device__ __forceinline__ uint32_t normalize(float (&oacc)[24], uint32_t r, uint32_t (&o)[48]) {
  const uint32_t ra = dup_lo(r), rb = dup_hi(r);
#pragma unroll
  for (int k = 0; k < 12; k++) o[12 * H + k] = hmul2(pack_bf16(oacc[2 * k], oacc[2 * k + 1]), (k & 1) ? rb : ra);
  return r - 0x2F802F80u;
}

struct Params {
  const __nv_bfloat16 *x, *wqkv, *wo, *rpb;
  const int* rp_idx;
  const __nv_bfloat16* mask;
  __nv_bfloat16* out;
  int nk_min, nk_rem, wstride, wskip, zero;
};
__device__ __forceinline__ float round_bf16(float v) { return __bfloat162float(__float2bfloat16(v)); }
__device__ __forceinline__ void redo_window(const Params& P, float* sm, int win, int rank) {
  float* xt = sm;
  float* qkv = sm + 192 * 64;
  const int tid = threadIdx.x;
  auto pixel = [&](int n) { return (size_t)(((8 * (win >> 6) + (n >> 3) + 4) & (IMG - 1)) * IMG + ((8 * (win & 63) + (n & 7) + 4) & (IMG - 1))) * CH; };
  auto gemm = [&](const __nv_bfloat16* w, int ldw, int ncols, auto&& put) {
    for (int e = tid; e < 4 * ncols; e += THREADS) {
      const int g = e / ncols, d = e - g * ncols;
      float acc[16];
#pragma unroll
      for (int i = 0; i < 16; i++) acc[i] = 0.f;
      for (int c = 0; c < CH; c++) {
        const float wv = __bfloat162float(w[c * ldw + d]);
#pragma unroll
        for (int i = 0; i < 16; i++) acc[i] = fmaf(xt[c * 64 + 16 * g + i], wv, acc[i]);
      }
#pragma unroll
      for (int i = 0; i < 16; i++) put(16 * g + i, d, acc[i]);
    }
  };
  __syncthreads();
  for (int e = tid; e < 64 * CH; e += THREADS) xt[(e % CH) * 64 + e / CH] = __bfloat162float(P.x[pixel(e / CH) + e % CH]);
  __syncthreads();
  gemm(P.wqkv, 3 * CH, 3 * CH, [&](int n, int d, float v) { qkv[n * 577 + d] = round_bf16(v); });
  __syncthreads();
  {
    const int n = tid & 63, h = tid >> 6;
    auto logit = [&](int m) {
      float s = 0.f;
      for (int d = 0; d < 48; d++) s = fmaf(qkv[n * 577 + 48 * h + d], qkv[m * 577 + CH + 48 * h + d], s);
      return s * SCALE + __bfloat162float(P.rpb[P.rp_idx[n * 64 + m] * 4 + h]) + __bfloat162float(P.mask[(size_t)win * 4096 + n * 64 + m]);
    };
    float mx = -INFINITY, sum = 0.f, o[48];
    for (int m = 0; m < 64; m++) mx = fmaxf(mx, logit(m));
#pragma unroll
    for (int d = 0; d < 48; d++) o[d] = 0.f;
    for (int m = 0; m < 64; m++) {
      const float p = expf(logit(m) - mx);
      sum += p;
#pragma unroll
      for (int d = 0; d < 48; d++) o[d] = fmaf(p, qkv[m * 577 + 2 * CH + 48 * h + d], o[d]);
    }
#pragma unroll
    for (int d = 0; d < 48; d++) xt[(48 * h + d) * 64 + n] = round_bf16(o[d] / sum);
  }
  __syncthreads();
  gemm(P.wo + 96 * rank, CH, 96, [&](int n, int d, float v) { P.out[pixel(n) + 96 * rank + d] = __float2bfloat16(v); });
}

#define HO 6
#define HQ 6
#define HV 6
#define E0 5
#define E1 15
#define ET 3
#define XSL "11110022220000"
#define XD 11
#define MS 8
#define KF 2
#define LF 9
#define NB 4
#define LAG 2
#define RA 0
#define QP 0
#define X1P 1
#define VP 2
#define X2P 4
#define K1W 1
#define HF 6
#define OF 5
#define SBM 0
#define TSB(i) do { if ((SBM >> (i)) & 1) sched(); TS(i); } while (0)
__host__ __device__ constexpr int g0(int r) { return r < 5 ? 3 * r : 16; }
__host__ __device__ constexpr int g1(int r) { return NB + (16 - NB) * r / 4; }
__host__ __device__ constexpr int xslot(int i) { return XSL[i] - '0'; }
__host__ __device__ constexpr int xbase(int i) { int b = 0; for (int q = 0; q < i; q++) b += xslot(q); return b; }
__host__ __device__ constexpr int xlast() { int l = 0; for (int q = 0; q < 14; q++) if (xslot(q)) l = q; return l; }
static_assert(xbase(14) == 12 && XD >= xlast(), "X schedule");

__global__ void __cluster_dims__(2, 1, 1) __launch_bounds__(THREADS, 1)
swin_attn_kernel(const __grid_constant__ CUtensorMap tm_x, const __grid_constant__ CUtensorMap tm_o, const __grid_constant__ CUtensorMap tm_w,
                 const __grid_constant__ CUtensorMap tm_wo, const __grid_constant__ Params P) {
  extern __shared__ __align__(1024) uint8_t smem_raw[];
  const uint32_t sbase = smem_u32(smem_raw);
  const int tid = threadIdx.x;
  const int wid = uniform(tid >> 5);
  const int j = wid >> 2, warp = wid & 3;
  const uint32_t lane = tid & 31;
  uint32_t rank;
  asm("mov.u32 %0, %%cluster_ctarank;" : "=r"(rank));
  auto load_w = [&](int part) {
#pragma unroll
    for (int h = 0; h < 2; h++) {
      const uint32_t b = sbase + B_W + (part == 0 && h == 0 ? 32 : 8 * part);
      if (part == 0 || h == 0) mbar_expect_tx(b, part == 0 ? W_HALF : W_PART);
      if (part < 3) tma_load3(sbase + OFF_W + part * W_PART + h * W_HALF, &tm_w, 96 * h, (part == 0 ? 6 : part == 1 ? 0 : 12) + 3 * rank, b);
      else tma_load3(sbase + WO + h * W_HALF, &tm_wo, 96 * (rank ^ h), 3 * rank, b);
    }
  };
  TS(38);
  uint32_t tab[4] = {0, 0, 0, 0};
  if ((wid >> 1) == 2) {
    const uint32_t* tp = reinterpret_cast<const uint32_t*>(P.rpb) + 2 * (tid - 128) + rank;
#pragma unroll
    for (int i = 0; i < 4; i++)
      if (i < 3 || tid < 128 + 33) asm volatile("ld.global.nc.u32 %0, [%1];" : "=r"(tab[i]) : "l"(tp + 128 * i) : "memory");
    if (elect_one()) {
      const uint32_t b = sbase + OFF_BAR + 128 * (wid & 1);
#pragma unroll
      for (uint32_t o = B_TOKEN; o <= B_LFREE; o += 8) mbar_init(b + o, 4);
      if (wid == 4) {
        mbar_arrive4(b + B_TOKEN);
        mbar_arrive4(b + B_KFREE);
        mbar_arrive4(b + B_VFREE);
      } else {
        mbar_init(sbase + B_DONE, 8);
      }
      asm volatile("fence.mbarrier_init.release.cluster;" ::: "memory");
    }
  } else {
    if (wid == 7 && lane < 18 && blockIdx.x < 128)
      asm volatile("prefetch.global.L2 [%0];" ::"l"((blockIdx.x < 96 ? reinterpret_cast<const uint8_t*>(P.wqkv) + blockIdx.x * 2304 : reinterpret_cast<const uint8_t*>(P.wo) + (blockIdx.x - 96) * 2304) + lane * 128) : "memory");
    if (elect_one()) {
      const uint32_t b0 = sbase + (j == 0 ? OFF_BAR + B_XFULL + 8 * warp : wid == 6 ? B_IDX : B_W);
      const uint32_t b1 = sbase + (j == 0 ? OFF_BAR + 128 + B_XFULL + 8 * warp : wid == 6 ? B_W + 8 : B_W + 32);
      const uint32_t b2 = sbase + (j == 0 ? OFF_BAR + 128 + B_X1 + 8 * warp : wid == 6 ? B_W + 16 : B_W + 24);
      mbar_init(b0, 1);
      mbar_init(b1, 1);
      mbar_init(b2, 1);
      if (j == 0) mbar_arrive(b1);
      fence_async_proxy();
      if (wid == 6) {
        mbar_expect_tx(sbase + B_IDX, 16384);
        bulk_load(sbase + WO, P.rp_idx, 16384, sbase + B_IDX);
      }
    }
  }
  __syncwarp();
  TS(39);
  const int cluster = blockIdx.x >> 1;
  const int nk = uniform(P.nk_min + (cluster < P.nk_rem) + (tid >> 10));
  const bool special = P.wskip != 0;
  const int nspecial = (!special || cluster < 4) ? 0 : cluster < 7 ? 3 : 2;
  const int wbase = !special ? cluster : cluster < 4 ? 63 * cluster : cluster < 7 ? 13 + 59 * cluster : 7 + 60 * cluster;
  auto window = [&](int k) { const int a = wbase + k * P.wstride; return a + (int)((uint32_t)(a * P.wskip) >> 20); };
  auto window_any = [&](int k) {
    const int v = k >= 2 ? 2 * (cluster - 5) + k : 120 + cluster, w = window(k < 4 ? k + nspecial : k), b = v < 64 ? 4032 + v : 64 * (v - 64) + 63;
    return (k >= 4 || k < 4 - nspecial) ? w : b;
  };
  int win = window_any(j);
  const uint8_t* mask_b = reinterpret_cast<const uint8_t*>(P.mask);
  const uint32_t quad_row = 32 * (warp >> 1) + 4 * (warp & 1);
  const uint8_t* mask_q0 = mask_b + quad_row * 128;
  MaskRows mr;
  TS(40);
  if (j == 0) {
    mr = mask_load(mask_q0 + (size_t)win * 8192 + lane * 16);
    load_tile(sbase + OFF_X + warp * 6144, warp, win, true, sbase + OFF_BAR + B_XFULL + 8 * warp, &tm_x);
  }
  if (wid == 7 && elect_one()) load_w(0);
  TS(24);
  if (sbase & 1023) __trap();
  const uint32_t bar = uniform(smem_u32(smem_raw) + OFF_BAR + (tid & 128)), bar_o = uniform(smem_u32(smem_raw) + OFF_BAR + ((tid & 128) ^ 128));
  const uint32_t xbar = uniform(smem_u32(smem_raw) + OFF_BAR + (tid & 128) + B_XFULL + 8 * ((tid >> 5) & 3));
  const uint32_t xbar_o = uniform(smem_u32(smem_raw) + OFF_BAR + ((tid & 128) ^ 128) + B_XFULL + 8 * ((tid >> 5) & 3));
  const uint32_t xdst = uniform(smem_u32(smem_raw) + OFF_X + ((tid >> 5) & 3) * 6144);
  const uint32_t x1off = j == 0 ? 0 : warp < 2 ? OFF_L + 12288 : WO + 16384 - 12288;
  auto loads = [&](int step) {
    if (j == 1) {
      if (QP == step && warp == 0 && elect_one()) load_w(1);
      if (X1P == step) load_tile(xdst + x1off, warp, win, true, xbar + B_X1, &tm_x);
      if (VP == step && warp == 2 && elect_one()) load_w(2);
      if (X2P == step) load_tile(xdst, warp, window_any(2), 2 < nk, xbar_o, &tm_x);
    }
  };
  asm volatile("st.shared.u32 [%0], %1;" ::"r"(sbase + OFF_FAIL + 4 * tid), "r"(0) : "memory");
  bool big = false;
  if ((wid >> 1) == 2) {
#pragma unroll
    for (int i = 0; i < 4; i++) {
      const float b0 = bf_lo(tab[i]) * LOG2E, b1 = bf_hi(tab[i]) * LOG2E;
      asm volatile("st.shared.u32 [%0], %1;" ::"r"(sbase + OFF_TAB + 4 * (tid - 128) + 256 * i), "r"(pack_bf16(ex2(b0), ex2(b1))) : "memory");
      big = big || !(fabsf(b0) <= 60.f && fabsf(b1) <= 60.f);
    }
  }
  TS(25);
  uint32_t force = __syncthreads_or(big) ? BAD_SUM : 0u;
  asm volatile("barrier.cluster.arrive.relaxed.aligned;" ::: "memory");
  TS(26);
  loads(0);
  TS(27);
  const uint32_t sb_a = uniform((sbase & 0x3FFFF) >> 4);
  const uint64_t w4 = desc_base<512, 2>(sb_a), k4 = desc_base<UB>(sb_a), v4 = desc_base<1024>(sb_a);
  const uint32_t blk = 2 * warp + ((lane >> 3) & 1);
  uint32_t stk = sbase + OFF_K + blk * UB + (lane >> 4) * 128 + (lane & 7) * 16;
  uint32_t stv = sbase + OFF_V + (lane >> 4) * 1024 + blk * 128 + (lane & 7) * 16;
  uint32_t xaddr0 = xdst + (lane & 15) * 128 + (((lane >> 4) ^ (lane & 7)) << 4);
  const uint32_t peer = rank ^ 1;
  const uint32_t area = uniform(smem_u32(smem_raw) + OFF_L + (tid >> 5) * 3072);
  const uint32_t r_bar = uniform(mapa(bar, peer)), r_area = uniform(mapa(area, peer));
  uint32_t l16 = lane * 16;
  uint32_t out_res = area + (lane & 15) * 64 + (((lane >> 4) ^ ((lane >> 1) & 3)) << 4);
  const uint32_t rzero = uniform(P.zero + (tid >> 10));
  const uint64_t mq = reinterpret_cast<uint64_t>(mask_b) + (32 * ((tid >> 6) & 1) + 4 * ((tid >> 5) & 1)) * 128;
  const uint8_t* mask_q = reinterpret_cast<const uint8_t*>(((uint64_t)uniform((uint32_t)(mq >> 32)) << 32) | uniform((uint32_t)mq));

  sched_barrier(stk, rzero); sched_barrier(stv, rzero); sched_barrier(xaddr0, rzero); sched_barrier(out_res, rzero); sched_barrier(l16, rzero);
  uint32_t xa[48], oo[48], eb0[16], eb1[16];
  auto fetch = [&](auto H) {
    constexpr int o = 24 + 12 * decltype(H)::v;
    const uint32_t addr = area + l16 + 1536 * decltype(H)::v;
    const uint4 x = lds128v(addr), y = lds128v(addr + 512), z = lds128v(addr + 1024);
    oo[o + 0] = x.x; oo[o + 1] = x.y; oo[o + 2] = x.z; oo[o + 3] = x.w; oo[o + 4] = y.x; oo[o + 5] = y.y; oo[o + 6] = y.z; oo[o + 7] = y.w;
    oo[o + 8] = z.x; oo[o + 9] = z.y; oo[o + 10] = z.z; oo[o + 11] = z.w;
  };
  auto store_out = [&](auto PP, float (&d)[48]) {
    constexpr int p = decltype(PP)::v;
    store_chunk<p>(((p & 1) ? (out_res ^ 32) : out_res) + (p >> 1) * 1024, d);
  };
  auto send_out = [&](int w, bool valid) {
    int row, col2;
    quad_origin(w, warp, valid, row, col2);
    if (elect_one()) tma_store5(&tm_o, row, col2, 3 * rank, area);
    asm volatile("cp.async.bulk.commit_group;" ::: "memory");
  };
  auto prefetch_mask = [&](int w) {
    if (elect_one()) prefetch_l2(mask_b + (size_t)w * 8192 + (rank * 4 + warp) * 1024, 1024);
  };
  auto prefetch_x = [&](int w) {
    if ((warp >> 1) == rank) {
      int row, col2;
      quad_origin(w, warp, true, row, col2);
      if (elect_one()) tma_prefetch5(&tm_x, row, col2);
    }
  };

  auto first_x = [&]() {
    uint32_t xaddr[4], all = ~0u;
#pragma unroll
    for (int q = 0; q < 4; q++) xaddr[q] = (xaddr0 + x1off) ^ (q << 5);
    mbar_wait(xbar + j * B_X1, 0);
    TS(29);
    static_for<12>([&](auto I) { read_x<decltype(I)::v>(xa, xaddr); all &= xa[4 * decltype(I)::v + 3]; });
    reads_done(all, sbase + OFF_DUMMY);
    TS(30);
  };
  auto gather = [&]() {
    const uint32_t odd = (l16 >> 6) & 1;
    const uint32_t ia = sbase + WO + (quad_row + 8 * (l16 >> 7) + odd) * 256 + (l16 & 0x30) * 2;
    mbar_wait(sbase + B_IDX, 0);
#pragma unroll
    for (int i = 0; i < 4; i++) {
      const int t = i >> 1, b = 4 * (i & 1);
      const uint4 u0 = lds128(ia + t * 512 + (i & 1) * 128 + odd * 16), u1 = lds128(ia + t * 512 + (i & 1) * 128 + 16 - odd * 16);
      const uint32_t id[8] = {u0.x, u0.y, u0.z, u0.w, u1.x, u1.y, u1.z, u1.w};
      uint32_t v[8];
#pragma unroll
      for (int q = 0; q < 8; q++) v[q] = lds32(sbase + OFF_TAB + 4 * id[q]);
#pragma unroll
      for (int q = 0; q < 4; q++) {
        const uint32_t x = odd ? v[(2 * q) ^ 4] : v[2 * q], y = odd ? v[(2 * q + 1) ^ 4] : v[2 * q + 1];
        eb0[2 * (b + q) + t] = __byte_perm(x, y, 0x5410);
        eb1[2 * (b + q) + t] = __byte_perm(x, y, 0x7632);
      }
    }
    TS(31);
  };
  gather();
#pragma unroll
  for (int i = 0; i < 16; i += 4) {
    asm volatile("{\n.reg .pred p;\nsetp.ne.u32 p, %4, 0;\n@p ld.shared.v4.u32 {%0,%1,%2,%3}, [%4];\n}\n" : "+r"(eb0[i]), "+r"(eb0[i + 1]), "+r"(eb0[i + 2]), "+r"(eb0[i + 3]) : "r"(rzero));
    asm volatile("{\n.reg .pred p;\nsetp.ne.u32 p, %4, 0;\n@p ld.shared.v4.u32 {%0,%1,%2,%3}, [%4];\n}\n" : "+r"(eb1[i]), "+r"(eb1[i + 1]), "+r"(eb1[i + 2]), "+r"(eb1[i + 3]) : "r"(rzero));
  }
  loads(1);
  TS(28);
#pragma unroll
  for (int h = 0; h < 2; h++) {
    constexpr uint32_t HI = 0x3E553E55u, LO = 0x396E396Eu;
    const uint32_t a = sbase + WK + h * 16384 + tid * 16;
    uint4 v[5];
    if (h == 0) mbar_wait(sbase + B_W + 32, 0);
    else mbar_wait(sbase + B_W, 0);
    TS(32 + h);
#pragma unroll
    for (int i = 0; i < 4 + h; i++) v[i] = lds128(a + i * 4096);
    loads(2 + h);
#pragma unroll
    for (int i = 0; i < 4 + h; i++)
      sts128(a + i * 4096, make_uint4(hfma2(v[i].x, HI, hmul2(v[i].x, LO)), hfma2(v[i].y, HI, hmul2(v[i].y, LO)),
                                      hfma2(v[i].z, HI, hmul2(v[i].z, LO)), hfma2(v[i].w, HI, hmul2(v[i].w, LO))));
  }
  fence_async_proxy();
  if (j == 0) first_x();
  TS(21);
  bool masked = false;
  if (j == 0) {
    pin_rows(mr);
    masked = __any_sync(0xffffffffu, mask_or(mr) != 0);
  }
  __syncthreads();
  TS(22);
  if (j == 1) {
    loads(4);
    mr = mask_load(mask_q0 + (size_t)win * 8192 + lane * 16);
    first_x();
    loads(5);
    wg_barrier(1);
    if (warp == 3 && elect_one()) load_w(3);
    if (2 < nk) prefetch_mask(window_any(2));
    if (3 < nk) {
      prefetch_x(window_any(3));
      prefetch_mask(window_any(3));
    }
    pin_rows(mr);
    masked = __any_sync(0xffffffffu, mask_or(mr) != 0);
  }

  uint32_t par = 0;
  auto sched = [&]() { sched_barrier(force, rzero); };
  int k = j, wprev = win, wnext = window_any(j + 2), wx = window_any(j + 3);
#pragma unroll
  for (int i = 0; i < 24; i++) oo[i] = 0;
  TS(23);
  for (;;) {
    float ca[48], cb[48], s0[32], s1[32];
    uint32_t qf[24];
    const int wnn = window(k + 4);
    bool ex0, ex1, kfree;
    TSB(1);
    fence_regs(xa);
    if (k == j) {
      if (K1W == 1 && j == 1) mbar_wait(bar + B_TOKEN, 0);
      gemm_phase<WK, 0, false>(ca, xa, w4, rzero, [&](auto) {});
      cluster_wait();
      if (K1W == 2 && j == 1) mbar_wait(bar + B_TOKEN, 0);
      mbar_wait(sbase + B_W + 8, 0);
      TS(35);
      gemm_phase<WQ, HF, false>(cb, xa, w4, rzero, [&](auto I) {
        constexpr int s = decltype(I)::v, p = s - (HF - 1);
        if constexpr (p == 0) { fence_regs(ca); mbar_wait(bar + B_KFREE, 0); TS(34); }
        if constexpr (p >= 0 && p < 6) store_chunk<(p >= 0 && p < 6) ? p : 0>(stk + p * 256, ca);
      });
      TS(36);
      mbar_wait(sbase + B_W + 16, 0);
      TS(37);
      if (j == 1) mbar_wait(sbase + B_W + 24, 0);
    } else {
      auto exchange = [&](auto G) {
        constexpr int g = decltype(G)::v;
        if constexpr (g == E0 - ET) ex0 = mbar_test(bar + B_EX0, par ^ 1);
        if constexpr (g == E1 - ET) ex1 = mbar_test(bar + B_EX1, par ^ 1);
        if constexpr (g == E0) { if (!ex0) mbar_wait(bar + B_EX0, par ^ 1); fetch(IC<0>{}); }
        if constexpr (g == E1) { if (!ex1) mbar_wait(bar + B_EX1, par ^ 1); fetch(IC<1>{}); }
      };
      gemm_phase<WK, 0, false>(cb, xa, w4, rzero, [&](auto I) { exchange(I); TSS(24 + decltype(I)::v); });
      TSB(2);
      gemm_phase<WO, HO, false>(ca, oo, w4, rzero, [&](auto I) {
        constexpr int s = decltype(I)::v, p = s - (HO - 1);
        if constexpr (p == -2) kfree = mbar_test(bar + B_KFREE, par);
        if constexpr (p == 0) { fence_regs(cb); TSB(3); if (!kfree) mbar_wait(bar + B_KFREE, par); }
        if constexpr (p >= 0 && p < 6) store_chunk<(p >= 0 && p < 6) ? p : 0>(stk + p * 256, cb);
        exchange(IC<12 + s>{});
        if constexpr (s == OF) wg_fence();
        if constexpr (s >= 0) TSS(36 + s);
      });
      gemm_phase<WQ, HQ, false>(cb, xa, w4, rzero, [&](auto I) {
        constexpr int s = decltype(I)::v, p = s - (HQ - 1);
        if constexpr (p == 0) { fence_regs(ca); TSB(4); }
        if constexpr (p >= 0 && p < 6) store_out(IC<(p >= 0 && p < 6) ? p : 0>{}, ca);
        if constexpr (s >= 0) TSS(48 + s);
      });
    }
    gemm_phase<WV, HV, true>(ca, xa, w4, rzero, [&](auto I) {
      constexpr int s = decltype(I)::v, p = s - (HV - 1);
      if constexpr (s == IDLE) {
        if (k + 4 < nk) {
          prefetch_mask(wnn);
          prefetch_x(wnn);
        }
        if (l16 == 0) {
          mbar_expect_tx(bar + B_EX0, 1536);
          mbar_expect_tx(bar + B_EX1, 1536);
        }
      }
      if constexpr (p == 0) { fence_regs(cb); TSB(6); }
      if constexpr (p >= 0 && p < 6) {
#pragma unroll
        for (int i = 4 * p; i < 4 * p + 4; i++) qf[i] = pack_bf16(cb[2 * i], cb[2 * i + 1]);
      }
      if constexpr (s >= 0) TSS(60 + s);
    });
    fence_regs(qf);
    fence_async_proxy();
    TSB(5);
    wg_barrier(j);
    wg_fence();
    issue_s<0>(s0, qf, k4);
    const bool vfree = mbar_test(bar + B_VFREE, par), xfull = mbar_test(xbar, par ^ 1);
    issue_s<1>(s1, qf, k4);
    if (l16 == 0) mbar_arrive(bar_o + B_TOKEN);
    TSB(7);
    send_out(wprev, k != j);
    uint32_t xaddr[4];
#pragma unroll
    for (int q = 0; q < 4; q++) xaddr[q] = xaddr0 ^ (q << 5);
    auto side = [&](auto R) {
      constexpr int r = decltype(R)::v, c = xslot(r), b = xbase(r);
      if constexpr (r == KF) {
        wg_wait<0>();
        fence_regs(s1);
        fence_regs(qf);
        if (l16 == 0) mbar_arrive(bar_o + B_KFREE);
      }
      if constexpr (r == LF) {
        asm volatile("cp.async.bulk.wait_group.read 0;" ::: "memory");
        __syncwarp();
        if (l16 == 0) mbar_arrive_remote_relaxed(r_bar + B_LFREE);
      }
      if constexpr (b == 0 && c > 0) { if (!xfull) mbar_wait(xbar, par ^ 1); TSB(19); }
      if constexpr (r == MS) mr = mask_load(offset_ptr(mask_q + (size_t)(k + 2 < nk ? wnext : win) * 8192, l16));
      static_for<c>([&](auto J) { read_x<b + decltype(J)::v>(xa, xaddr); });
      if constexpr (r == XD) {
        uint32_t all = ~0u;
#pragma unroll
        for (int i = 12 - xslot(xlast()); i < 12; i++) all &= xa[4 * i + 3];
        reads_done(all, sbase + OFF_DUMMY);
        load_tile(xdst, warp, wx, k + 3 < nk, xbar_o, &tm_x);
        TSB(15);
      }
    };
    auto store_v = [&](auto PP) { store_chunk<decltype(PP)::v>(stv + decltype(PP)::v * 2048, ca); };
    float o0[24], o1[24];
    uint32_t p0[16], p1[16], z0[6], z1[6], r0, r1;
    RowSums l0, l1;
    if (!vfree) mbar_wait(bar + B_VFREE, par);
    wg_wait<2>();
    fence_regs(ca);
    fence_regs(xa);
    TSB(8);
    store_v(IC<0>{});
    side(IC<0>{});
    store_v(IC<1>{});
    wg_wait<1>();
    fence_regs(s0);
    TSB(9);
    static_for<5>([&](auto R) {
      constexpr int r = decltype(R)::v;
      side(IC<1 + r>{});
      if constexpr (r == 0) {
        if (masked) {
          uint32_t l = l16;
          asm volatile("" : "+r"(l));
          const uint8_t* mp = offset_ptr(mask_q + (size_t)win * 8192, (l & 0x180) * 8 + (l & 0x40) * 2 + (l & 0x30));
          wg_wait<0>();
          fence_regs(s0);
          fence_regs(s1);
          const uint4 m[4] = {ldg128(mp), ldg128(mp + 64), ldg128(mp + 256), ldg128(mp + 320)};
          add_mask(s0, s1, m);
          if (__any_sync(0xffffffffu, force != 0)) {
            subtract_row_max(s0);
            subtract_row_max(s1);
          }
        }
      }
      if constexpr (r < 4) store_v(IC<(r < 4 ? r + 2 : 0)>{});
      exp_pairs<g0(r), g0(r + 1)>(s0);
      pack_pairs<(g0(r) > LAG ? g0(r) - LAG : 0), g0(r + 1) - LAG>(s0, eb0, p0, z0);
      sched();
    });
    TSB(10);
    fence_async_proxy();
    exp_pairs<0, NB>(s1);
    pack_pairs<16 - LAG, 16>(s0, eb0, p0, z0);
    pack_pairs<0, (NB > LAG ? NB - LAG : 0)>(s1, eb1, p1, z1);
    l0.start(z0);
    sched();
    wg_barrier(j);
    side(IC<6>{});
    wg_fence();
    issue_pv<0>(o0, p0, v4);
    sched();
    TSB(11);
    static_for<4>([&](auto R) {
      constexpr int r = decltype(R)::v;
      if constexpr (r == RA) r0 = l0.finish();
      side(IC<7 + r>{});
      exp_pairs<g1(r), g1(r + 1)>(s1);
      pack_pairs<(g1(r) > LAG ? g1(r) - LAG : 0), (r < 3 ? g1(r + 1) - LAG : 16)>(s1, eb1, p1, z1);
      if (r < 3) sched();
    });
    TSB(12);
    wg_fence();
    issue_pv<1>(o1, p1, v4);
    sched();
    l1.start(z1);
    side(IC<11>{});
    wg_wait<1>();
    fence_regs(o0);
    fence_regs(p0);
    TSB(13);
    uint32_t bad = normalize<0>(o0, r0, oo);
    mbar_wait(bar + B_LFREE, par);
#pragma unroll
    for (int q = 0; q < 3; q++) st_async16(r_area + l16 + q * 512, oo[4 * q], oo[4 * q + 1], oo[4 * q + 2], oo[4 * q + 3], r_bar + B_EX0);
    TSB(14);
    sched();
    r1 = l1.finish();
    side(IC<12>{});
    wg_wait<0>();
    fence_regs(o1);
    fence_regs(p1);
    TSB(16);
    if (l16 == 0) mbar_arrive(bar_o + B_VFREE);
    bad = ((bad | normalize<1>(o1, r1, oo)) & BAD_SUM) | force;
#pragma unroll
    for (int q = 3; q < 6; q++) st_async16(r_area + l16 + q * 512, oo[4 * q], oo[4 * q + 1], oo[4 * q + 2], oo[4 * q + 3], r_bar + B_EX1);
    sched();
    TSB(17);
    side(IC<13>{});
    pin_rows(mr);
    masked = __any_sync(0xffffffffu, (mask_or(mr) | bad) != 0);
    if (masked && __any_sync(0xffffffffu, (bad & BAD_SUM) != 0)) {
      force |= 1;
      if ((l16 >> 4) == (uint32_t)(k >> 6)) asm volatile("red.shared.or.b32 [%0], %1;" ::"r"(sbase + OFF_FAIL + 512 * j + 128 * warp + (l16 >> 2)), "r"(1u << ((k >> 1) & 31)) : "memory");
    }
    wprev = win;
    win = wnext;
    wnext = wnn;
    wx = window(k + 5);
    k += 2;
    if (k >= nk) break;
    par ^= 1;
    TSB(18);
    TS_SET(k);
    TSB(0);
    mbar_wait(bar + B_TOKEN, par);
  }
  {
    const uint32_t a = sbase + OFF_FAIL + 512 * j + 128 * warp + (l16 >> 2);
    st_async4(mapa(a + 1024, peer), lds32(a), mapa(sbase + B_DONE, peer));
    __syncwarp();
    if (l16 == 0) mbar_expect_tx(sbase + B_DONE, 128);
  }
  {
    float ca[48];
    mbar_wait(sbase + B_W + 24, 0);
    gemm_phase<WO, 0, false>(ca, oo, w4, rzero, [&](auto I) {
      constexpr int s = decltype(I)::v;
      if constexpr (s == 5) { mbar_wait(bar + B_EX0, par); fetch(IC<0>{}); wg_fence(); }
      if constexpr (s == 8) { mbar_wait(bar + B_EX1, par); fetch(IC<1>{}); wg_fence(); }
    });
    wg_wait<0>();
    fence_regs(ca);
    fence_regs(oo);
    static_for<6>([&](auto PP) { store_out(PP, ca); });
    fence_async_proxy();
    __syncwarp();
    send_out(wprev, true);
  }
  TS(21);
  if (k == nk + 1) mbar_wait(xbar_o, j ? par : par ^ 1);
  mbar_wait(sbase + B_DONE, 0);
  uint32_t failed = 0;
#pragma unroll
  for (int i = 0; i < 4; i++) {
    const uint4 f = lds128(sbase + OFF_FAIL + 512 * i + l16);
    failed |= f.x | f.y | f.z | f.w;
  }
  if (__any_sync(0xffffffffu, failed != 0)) {
    asm volatile("cp.async.bulk.wait_group 0;" ::: "memory");
    asm volatile("fence.proxy.async;" ::: "memory");
    for (int kk = 0; kk < nk; kk++) {
      uint32_t f = 0;
      for (int i = 0; i < 8; i++) f |= lds32(sbase + OFF_FAIL + 1024 * (i >> 2) + 512 * (kk & 1) + 128 * (i & 3) + 4 * (kk >> 6));
      if ((f >> ((kk >> 1) & 31)) & 1) redo_window(P, reinterpret_cast<float*>(smem_raw), window_any(kk), rank);
    }
  }
  asm volatile("cp.async.bulk.wait_group.read 0;" ::: "memory");
  TS(22);
}

typedef CUresult (*EncodeTiledFn)(CUtensorMap*, CUtensorMapDataType, cuuint32_t, void*, const cuuint64_t*, const cuuint64_t*,
                                  const cuuint32_t*, const cuuint32_t*, CUtensorMapInterleave, CUtensorMapSwizzle,
                                  CUtensorMapL2promotion, CUtensorMapFloatOOBfill);

void encode_image_map(EncodeTiledFn fn, CUtensorMap* tm, void* ptr, uint32_t group_c, CUtensorMapSwizzle sw) {
  const cuuint64_t dims[5] = {(cuuint64_t)group_c, 2, (cuuint64_t)IMG, (cuuint64_t)IMG / 2, (cuuint64_t)(CH / group_c)};
  const cuuint64_t strides[4] = {(cuuint64_t)CH * 2, (cuuint64_t)CH * 2 * IMG, (cuuint64_t)CH * 4, (cuuint64_t)group_c * 2};
  const cuuint32_t box[5] = {group_c, 2, 4, 2, 3};
  const cuuint32_t estr[5] = {1, 1, 1, 1, 1};
  fn(tm, CU_TENSOR_MAP_DATA_TYPE_BFLOAT16, 5, ptr, dims, strides, box, estr, CU_TENSOR_MAP_INTERLEAVE_NONE, sw,
     CU_TENSOR_MAP_L2_PROMOTION_L2_128B, CU_TENSOR_MAP_FLOAT_OOB_FILL_NONE);
}
void encode_weight_map(EncodeTiledFn fn, CUtensorMap* tm, void* ptr, uint32_t cols) {
  const cuuint64_t dims[3] = {32, (cuuint64_t)CH, (cuuint64_t)(cols / 32)};
  const cuuint64_t strides[2] = {(cuuint64_t)cols * 2, 64};
  const cuuint32_t box[3] = {32, 96, 3};
  const cuuint32_t estr[3] = {1, 1, 1};
  fn(tm, CU_TENSOR_MAP_DATA_TYPE_BFLOAT16, 3, ptr, dims, strides, box, estr, CU_TENSOR_MAP_INTERLEAVE_NONE, CU_TENSOR_MAP_SWIZZLE_64B,
     CU_TENSOR_MAP_L2_PROMOTION_L2_128B, CU_TENSOR_MAP_FLOAT_OOB_FILL_NONE);
}

}

extern "C" void kernel_launch(void* const* d_in, const int* in_sizes, int n_in, void* d_out, int out_size) {
  (void)in_sizes; (void)n_in; (void)out_size;
  static int nclusters = 0;
  static EncodeTiledFn encode = nullptr;
  if (nclusters == 0) {
    cudaFuncSetAttribute(swin_attn_kernel, cudaFuncAttributeMaxDynamicSharedMemorySize, SMEM_BYTES);
    int dev = 0, sms = 0;
    cudaGetDevice(&dev);
    cudaDeviceGetAttribute(&sms, cudaDevAttrMultiProcessorCount, dev);
    nclusters = sms / 2;
    cudaLaunchConfig_t cfg = {};
    cfg.gridDim = dim3(2 * nclusters);
    cfg.blockDim = dim3(THREADS);
    cfg.dynamicSmemBytes = SMEM_BYTES;
    cudaLaunchAttribute at[1];
    at[0].id = cudaLaunchAttributeClusterDimension;
    at[0].val.clusterDim.x = 2; at[0].val.clusterDim.y = 1; at[0].val.clusterDim.z = 1;
    cfg.attrs = at; cfg.numAttrs = 1;
    int maxc = 0;
    if (cudaOccupancyMaxActiveClusters(&maxc, swin_attn_kernel, &cfg) == cudaSuccess && maxc > 0 && maxc < nclusters) nclusters = maxc;
    (void)cudaGetLastError();
    void* fn = nullptr;
    cudaDriverEntryPointQueryResult qres;
    cudaGetDriverEntryPoint("cuTensorMapEncodeTiled", &fn, cudaEnableDefault, &qres);
    encode = (EncodeTiledFn)fn;
  }
  CUtensorMap tm_x, tm_o, tm_w, tm_wo;
  encode_image_map(encode, &tm_x, d_in[0], 64, CU_TENSOR_MAP_SWIZZLE_128B);
  encode_image_map(encode, &tm_o, d_out, 32, CU_TENSOR_MAP_SWIZZLE_64B);
  encode_weight_map(encode, &tm_w, d_in[1], 3 * CH);
  encode_weight_map(encode, &tm_wo, d_in[2], CH);
  Params P;
  P.x = (const __nv_bfloat16*)d_in[0];
  P.wqkv = (const __nv_bfloat16*)d_in[1];
  P.wo = (const __nv_bfloat16*)d_in[2];
  P.rpb = (const __nv_bfloat16*)d_in[3];
  P.rp_idx = (const int*)d_in[4];
  P.mask = (const __nv_bfloat16*)d_in[5];
  P.out = (__nv_bfloat16*)d_out;
  P.wstride = nclusters == 66 ? 1 : nclusters;
  P.wskip = nclusters == 66 ? 16645 : 0;
  P.zero = 0;
  P.nk_min = NWIN / nclusters;
  P.nk_rem = NWIN % nclusters;
  swin_attn_kernel<<<2 * nclusters, THREADS, SMEM_BYTES, cudaStreamPerThread>>>(tm_x, tm_o, tm_w, tm_wo, P);
}
```

```cpp
#include <cuda_runtime.h>
#include <cuda_bf16.h>
#include <cuda.h>
#include <stdint.h>

namespace {

constexpr int IMG = 512, CH = 192, NWIN = 4096;
constexpr int THREADS = 256;

constexpr uint32_t OFF_X = 0;
constexpr uint32_t OFF_K = 24576;
constexpr uint32_t UB = 1536;
constexpr uint32_t OFF_V = OFF_K + 12288;
constexpr uint32_t OFF_L = OFF_V + 12288;
constexpr uint32_t OFF_W = OFF_L + 2 * 12288;
constexpr uint32_t W_HALF = 3 * 96 * 64, W_PART = 2 * W_HALF;
constexpr uint32_t WK = OFF_W, WQ = OFF_W + W_PART, WV = OFF_W + 2 * W_PART, WO = OFF_W + 3 * W_PART;
constexpr uint32_t OFF_BAR = OFF_W + 4 * W_PART;
constexpr uint32_t B_XFULL = 0;
constexpr uint32_t B_TOKEN = 32;
constexpr uint32_t B_KFREE = 40, B_VFREE = 48;
constexpr uint32_t B_EX0 = 56, B_EX1 = 64;
constexpr uint32_t B_LFREE = 72;
constexpr uint32_t B_X1 = 80;
constexpr uint32_t B_W = OFF_BAR + 256;
constexpr uint32_t B_IDX = OFF_BAR + 296;
constexpr uint32_t B_DONE = OFF_BAR + 304;
constexpr uint32_t OFF_DUMMY = OFF_BAR + 320;
constexpr uint32_t OFF_FAIL = OFF_BAR + 384;
constexpr uint32_t OFF_TAB = OFF_FAIL + 2048;
constexpr uint32_t OFF_END = OFF_TAB + 1024;
constexpr uint32_t SMEM_BYTES = OFF_END;

constexpr float LOG2E = 1.4426950408889634f;
constexpr float SCALE = 0.14433756729740643f;

__device__ __forceinline__ uint32_t smem_u32(const void* p) { return (uint32_t)__cvta_generic_to_shared(p); }
__device__ __forceinline__ void wg_fence() { asm volatile("wgmma.fence.sync.aligned;" ::: "memory"); }
__device__ __forceinline__ void wg_commit() { asm volatile("wgmma.commit_group.sync.aligned;" ::: "memory"); }
template <int N> __device__ __forceinline__ void wg_wait() { asm volatile("wgmma.wait_group.sync.aligned %0;" ::"n"(N) : "memory"); }
template <int N> __device__ __forceinline__ void fence_regs(float (&d)[N]) {
#pragma unroll
  for (int i = 0; i < N; i++) asm volatile("" : "+f"(d[i])::"memory");
}
template <int N> __device__ __forceinline__ void fence_regs(uint32_t (&d)[N]) {
#pragma unroll
  for (int i = 0; i < N; i++) asm volatile("" : "+r"(d[i])::"memory");
}
__device__ __forceinline__ bool elect_one() {
  uint32_t pred;
  asm volatile("{\n.reg .pred p;\nelect.sync _|p, 0xffffffff;\nselp.u32 %0, 1, 0, p;\n}\n" : "=r"(pred));
  return pred != 0;
}
__device__ __forceinline__ uint32_t pack_bf16(float lo, float hi) {
  uint32_t r;
  asm("cvt.rn.bf16x2.f32 %0, %1, %2;" : "=r"(r) : "f"(hi), "f"(lo));
  return r;
}
__device__ __forceinline__ float bf_lo(uint32_t v) { return __uint_as_float(v << 16); }
__device__ __forceinline__ float bf_hi(uint32_t v) { return __uint_as_float(v & 0xffff0000u); }
__device__ __forceinline__ float ex2(float x) {
  float y;
  asm("ex2.approx.ftz.f32 %0, %1;" : "=f"(y) : "f"(x));
  return y;
}
__device__ __forceinline__ uint32_t hadd2(uint32_t a, uint32_t b) {
  uint32_t r;
  asm("add.rn.bf16x2 %0, %1, %2;" : "=r"(r) : "r"(a), "r"(b));
  return r;
}
__device__ __forceinline__ uint32_t hmul2(uint32_t a, uint32_t b) {
  uint32_t r;
  asm("mul.rn.bf16x2 %0, %1, %2;" : "=r"(r) : "r"(a), "r"(b));
  return r;
}
__device__ __forceinline__ uint32_t dup_lo(uint32_t a) {
  uint32_t r;
  asm("{\n.reg .b16 l, h;\nmov.b32 {l, h}, %1;\nmov.b32 %0, {l, l};\n}\n" : "=r"(r) : "r"(a));
  return r;
}
__device__ __forceinline__ uint32_t dup_hi(uint32_t a) {
  uint32_t r;
  asm("{\n.reg .b16 l, h;\nmov.b32 {l, h}, %1;\nmov.b32 %0, {h, h};\n}\n" : "=r"(r) : "r"(a));
  return r;
}
__device__ __forceinline__ float rcp_approx(float x) {
  float y;
  asm("rcp.approx.ftz.f32 %0, %1;" : "=f"(y) : "f"(x));
  return y;
}
__device__ __forceinline__ uint4 ldg128(const void* p) {
  uint4 v;
  asm volatile("ld.global.L1::evict_normal.v4.u32 {%0,%1,%2,%3}, [%4];" : "=r"(v.x), "=r"(v.y), "=r"(v.z), "=r"(v.w) : "l"(p) : "memory");
  return v;
}
__device__ __forceinline__ void prefetch_l2(const void* p, uint32_t bytes) {
  asm volatile("cp.async.bulk.prefetch.L2.global [%0], %1;" ::"l"(p), "r"(bytes) : "memory");
}
__device__ __forceinline__ uint4 lds128(uint32_t addr) {
  uint4 v;
  asm volatile("ld.shared.v4.u32 {%0,%1,%2,%3}, [%4];" : "=r"(v.x), "=r"(v.y), "=r"(v.z), "=r"(v.w) : "r"(addr) : "memory");
  return v;
}
__device__ __forceinline__ uint4 lds128v(uint32_t addr) {
  uint4 v;
  asm volatile("ld.volatile.shared.v4.u32 {%0,%1,%2,%3}, [%4];" : "=r"(v.x), "=r"(v.y), "=r"(v.z), "=r"(v.w) : "r"(addr) : "memory");
  return v;
}
__device__ __forceinline__ uint32_t lds32(uint32_t addr) {
  uint32_t v;
  asm volatile("ld.shared.u32 %0, [%1];" : "=r"(v) : "r"(addr) : "memory");
  return v;
}
__device__ __forceinline__ void stmatrix_x4(uint32_t addr, uint32_t a, uint32_t b, uint32_t c, uint32_t d) {
  asm volatile("stmatrix.sync.aligned.m8n8.x4.shared.b16 [%0], {%1,%2,%3,%4};" ::"r"(addr), "r"(a), "r"(b), "r"(c), "r"(d) : "memory");
}
__device__ __forceinline__ void ldmatrix_x4(uint32_t addr, uint32_t& a, uint32_t& b, uint32_t& c, uint32_t& d) {
  asm volatile("ldmatrix.sync.aligned.m8n8.x4.shared.b16 {%0,%1,%2,%3}, [%4];" : "=r"(a), "=r"(b), "=r"(c), "=r"(d) : "r"(addr) : "memory");
}
__device__ __forceinline__ void fence_async_proxy() {
  asm volatile("fence.proxy.async.shared::cta;" ::: "memory");
}
__device__ __forceinline__ void wg_barrier(int j) { asm volatile("bar.sync %0, 128;" ::"r"(1 + j) : "memory"); }
__device__ __forceinline__ void cluster_wait() { asm volatile("barrier.cluster.wait.acquire.aligned;" ::: "memory"); }
__device__ __forceinline__ uint32_t mapa(uint32_t a, uint32_t rank) {
  uint32_t o;
  asm("mapa.shared::cluster.u32 %0, %1, %2;" : "=r"(o) : "r"(a), "r"(rank));
  return o;
}
__device__ __forceinline__ void mbar_init(uint32_t a, uint32_t cnt) { asm volatile("mbarrier.init.shared::cta.b64 [%0], %1;" ::"r"(a), "r"(cnt) : "memory"); }
__device__ __forceinline__ void mbar_expect_tx(uint32_t a, uint32_t tx) {
  asm volatile("mbarrier.arrive.expect_tx.shared::cta.b64 _, [%0], %1;" ::"r"(a), "r"(tx) : "memory");
}
__device__ __forceinline__ void mbar_arrive(uint32_t a) { asm volatile("mbarrier.arrive.shared::cta.b64 _, [%0];" ::"r"(a) : "memory"); }
__device__ __forceinline__ void mbar_arrive4(uint32_t a) { asm volatile("mbarrier.arrive.shared::cta.b64 _, [%0], 4;" ::"r"(a) : "memory"); }
__device__ __forceinline__ uint32_t uniform(uint32_t v) { return __shfl_sync(0xffffffffu, v, 0); }
__device__ __forceinline__ void mbar_arrive_remote_relaxed(uint32_t a) {
  asm volatile("mbarrier.arrive.relaxed.cluster.shared::cluster.b64 _, [%0];" ::"r"(a) : "memory");
}
__device__ __forceinline__ void mbar_wait(uint32_t a, uint32_t parity) {
  asm volatile(
      "{\n.reg .pred p;\n.reg .u32 n;\n"
      "mbarrier.try_wait.parity.shared::cta.b64 p, [%0], %1;\n"
      "@p bra WAIT_DONE;\n"
      "mov.u32 n, 0;\n"
      "WAIT_LOOP:\n"
      "add.u32 n, n, 1;\n"
      "setp.gt.u32 p, n, 4000000;\n"
      "@p trap;\n"
      "mbarrier.try_wait.parity.shared::cta.b64 p, [%0], %1;\n"
      "@!p bra WAIT_LOOP;\n"
      "WAIT_DONE:\n}\n" ::"r"(a), "r"(parity) : "memory");
}
__device__ __forceinline__ bool mbar_test(uint32_t a, uint32_t parity) {
  uint32_t ok;
  asm volatile("{\n.reg .pred p;\nmbarrier.test_wait.parity.shared::cta.b64 p, [%1], %2;\nselp.u32 %0, 1, 0, p;\n}\n" : "=r"(ok) : "r"(a), "r"(parity) : "memory");
  return ok != 0;
}
__device__ __forceinline__ uint32_t hfma2(uint32_t a, uint32_t b, uint32_t c) {
  uint32_t r;
  asm("fma.rn.bf16x2 %0, %1, %2, %3;" : "=r"(r) : "r"(a), "r"(b), "r"(c));
  return r;
}
__device__ __forceinline__ void st_async16(uint32_t raddr, uint32_t a, uint32_t b, uint32_t c, uint32_t d, uint32_t rbar) {
  asm volatile("st.async.weak.shared::cluster.mbarrier::complete_tx::bytes.v4.b32 [%0], {%1,%2,%3,%4}, [%5];" ::"r"(raddr),
               "r"(a), "r"(b), "r"(c), "r"(d), "r"(rbar) : "memory");
}

__device__ __forceinline__ void st_async4(uint32_t raddr, uint32_t v, uint32_t rbar) {
  asm volatile("st.async.weak.shared::cluster.mbarrier::complete_tx::bytes.b32 [%0], %1, [%2];" ::"r"(raddr), "r"(v), "r"(rbar) : "memory");
}
__device__ __forceinline__ void sts128(uint32_t addr, uint4 v) {
  asm volatile("st.shared.v4.u32 [%0], {%1,%2,%3,%4};" ::"r"(addr), "r"(v.x), "r"(v.y), "r"(v.z), "r"(v.w) : "memory");
}
__device__ __forceinline__ void bulk_load(uint32_t dst, const void* src, uint32_t bytes, uint32_t bar) {
  asm volatile("cp.async.bulk.shared::cta.global.mbarrier::complete_tx::bytes [%0], [%1], %2, [%3];" ::"r"(dst), "l"(src),
               "r"(bytes), "r"(bar) : "memory");
}
__device__ __forceinline__ void tma_load3(uint32_t dst, const CUtensorMap* tm, int c1, int c2, uint32_t bar) {
  asm volatile("cp.async.bulk.tensor.3d.shared::cta.global.tile.mbarrier::complete_tx::bytes [%0], [%1, {0, %2, %3}], [%4];" ::"r"(dst),
               "l"(tm), "r"(c1), "r"(c2), "r"(bar) : "memory");
}
__device__ __forceinline__ void tma_load5(uint32_t dst, const CUtensorMap* tm, int c2, int c3, uint32_t bar) {
  asm volatile("cp.async.bulk.tensor.5d.shared::cta.global.tile.mbarrier::complete_tx::bytes [%0], [%1, {0, 0, %2, %3, 0}], [%4];" ::"r"(dst),
               "l"(tm), "r"(c2), "r"(c3), "r"(bar) : "memory");
}
__device__ __forceinline__ void tma_store5(const CUtensorMap* tm, int c2, int c3, int c4, uint32_t src, uint64_t policy) {
  asm volatile("cp.async.bulk.tensor.5d.global.shared::cta.tile.bulk_group.L2::cache_hint [%0, {0, 0, %1, %2, %3}], [%4], %5;" ::"l"(tm),
               "r"(c2), "r"(c3), "r"(c4), "r"(src), "l"(policy) : "memory");
}
__device__ __forceinline__ void sched_barrier(uint32_t& t, uint32_t zero) {
  asm volatile("{\n.reg .pred p;\nsetp.ne.u32 p, %1, 0;\n@p mov.u32 %0, %%clock;\n}\n" : "+r"(t) : "r"(zero) : "memory");
}

__device__ __forceinline__ void wgmma_n48_a(float (&d)[24], uint32_t a0, uint32_t a1, uint32_t a2, uint32_t a3, uint64_t db) {
  asm volatile("{\n.reg .pred p;\nsetp.ne.b32 p, 1, 0;\n"
      "wgmma.mma_async.sync.aligned.m64n48k16.f32.bf16.bf16 "
      "{%0,%1,%2,%3,%4,%5,%6,%7,%8,%9,%10,%11,%12,%13,%14,%15,"
      "%16,%17,%18,%19,%20,%21,%22,%23}, "
      "{%24,%25,%26,%27}, %28, p, 1, 1, 1;\n}\n"
      : "+f"(d[0]), "+f"(d[1]), "+f"(d[2]), "+f"(d[3]), "+f"(d[4]), "+f"(d[5]), "+f"(d[6]), "+f"(d[7]),
        "+f"(d[8]), "+f"(d[9]), "+f"(d[10]), "+f"(d[11]), "+f"(d[12]), "+f"(d[13]), "+f"(d[14]), "+f"(d[15]),
        "+f"(d[16]), "+f"(d[17]), "+f"(d[18]), "+f"(d[19]), "+f"(d[20]), "+f"(d[21]), "+f"(d[22]), "+f"(d[23])
      : "r"(a0), "r"(a1), "r"(a2), "r"(a3), "l"(db));
}
__device__ __forceinline__ void wgmma_n48_z(float (&d)[24], uint32_t a0, uint32_t a1, uint32_t a2, uint32_t a3, uint64_t db) {
  asm volatile("{\n.reg .pred p;\nsetp.ne.b32 p, 0, 0;\n"
      "wgmma.mma_async.sync.aligned.m64n48k16.f32.bf16.bf16 "
      "{%0,%1,%2,%3,%4,%5,%6,%7,%8,%9,%10,%11,%12,%13,%14,%15,"
      "%16,%17,%18,%19,%20,%21,%22,%23}, "
      "{%24,%25,%26,%27}, %28, p, 1, 1, 1;\n}\n"
      : "=f"(d[0]), "=f"(d[1]), "=f"(d[2]), "=f"(d[3]), "=f"(d[4]), "=f"(d[5]), "=f"(d[6]), "=f"(d[7]),
        "=f"(d[8]), "=f"(d[9]), "=f"(d[10]), "=f"(d[11]), "=f"(d[12]), "=f"(d[13]), "=f"(d[14]), "=f"(d[15]),
        "=f"(d[16]), "=f"(d[17]), "=f"(d[18]), "=f"(d[19]), "=f"(d[20]), "=f"(d[21]), "=f"(d[22]), "=f"(d[23])
      : "r"(a0), "r"(a1), "r"(a2), "r"(a3), "l"(db));
}
__device__ __forceinline__ void wgmma_n96_a(float (&d)[48], uint32_t a0, uint32_t a1, uint32_t a2, uint32_t a3, uint64_t db) {
  asm volatile("{\n.reg .pred p;\nsetp.ne.b32 p, 1, 0;\n"
      "wgmma.mma_async.sync.aligned.m64n96k16.f32.bf16.bf16 "
      "{%0,%1,%2,%3,%4,%5,%6,%7,%8,%9,%10,%11,%12,%13,%14,%15,"
      "%16,%17,%18,%19,%20,%21,%22,%23,%24,%25,%26,%27,%28,%29,%30,%31,"
      "%32,%33,%34,%35,%36,%37,%38,%39,%40,%41,%42,%43,%44,%45,%46,%47}, "
      "{%48,%49,%50,%51}, %52, p, 1, 1, 1;\n}\n"
      : "+f"(d[0]), "+f"(d[1]), "+f"(d[2]), "+f"(d[3]), "+f"(d[4]), "+f"(d[5]), "+f"(d[6]), "+f"(d[7]),
        "+f"(d[8]), "+f"(d[9]), "+f"(d[10]), "+f"(d[11]), "+f"(d[12]), "+f"(d[13]), "+f"(d[14]), "+f"(d[15]),
        "+f"(d[16]), "+f"(d[17]), "+f"(d[18]), "+f"(d[19]), "+f"(d[20]), "+f"(d[21]), "+f"(d[22]), "+f"(d[23]),
        "+f"(d[24]), "+f"(d[25]), "+f"(d[26]), "+f"(d[27]), "+f"(d[28]), "+f"(d[29]), "+f"(d[30]), "+f"(d[31]),
        "+f"(d[32]), "+f"(d[33]), "+f"(d[34]), "+f"(d[35]), "+f"(d[36]), "+f"(d[37]), "+f"(d[38]), "+f"(d[39]),
        "+f"(d[40]), "+f"(d[41]), "+f"(d[42]), "+f"(d[43]), "+f"(d[44]), "+f"(d[45]), "+f"(d[46]), "+f"(d[47])
      : "r"(a0), "r"(a1), "r"(a2), "r"(a3), "l"(db));
}
__device__ __forceinline__ void wgmma_n96_z(float (&d)[48], uint32_t a0, uint32_t a1, uint32_t a2, uint32_t a3, uint64_t db) {
  asm volatile("{\n.reg .pred p;\nsetp.ne.b32 p, 0, 0;\n"
      "wgmma.mma_async.sync.aligned.m64n96k16.f32.bf16.bf16 "
      "{%0,%1,%2,%3,%4,%5,%6,%7,%8,%9,%10,%11,%12,%13,%14,%15,"
      "%16,%17,%18,%19,%20,%21,%22,%23,%24,%25,%26,%27,%28,%29,%30,%31,"
      "%32,%33,%34,%35,%36,%37,%38,%39,%40,%41,%42,%43,%44,%45,%46,%47}, "
      "{%48,%49,%50,%51}, %52, p, 1, 1, 1;\n}\n"
      : "=f"(d[0]), "=f"(d[1]), "=f"(d[2]), "=f"(d[3]), "=f"(d[4]), "=f"(d[5]), "=f"(d[6]), "=f"(d[7]),
        "=f"(d[8]), "=f"(d[9]), "=f"(d[10]), "=f"(d[11]), "=f"(d[12]), "=f"(d[13]), "=f"(d[14]), "=f"(d[15]),
        "=f"(d[16]), "=f"(d[17]), "=f"(d[18]), "=f"(d[19]), "=f"(d[20]), "=f"(d[21]), "=f"(d[22]), "=f"(d[23]),
        "=f"(d[24]), "=f"(d[25]), "=f"(d[26]), "=f"(d[27]), "=f"(d[28]), "=f"(d[29]), "=f"(d[30]), "=f"(d[31]),
        "=f"(d[32]), "=f"(d[33]), "=f"(d[34]), "=f"(d[35]), "=f"(d[36]), "=f"(d[37]), "=f"(d[38]), "=f"(d[39]),
        "=f"(d[40]), "=f"(d[41]), "=f"(d[42]), "=f"(d[43]), "=f"(d[44]), "=f"(d[45]), "=f"(d[46]), "=f"(d[47])
      : "r"(a0), "r"(a1), "r"(a2), "r"(a3), "l"(db));
}
__device__ __forceinline__ void wgmma_n96_p(float (&d)[48], uint32_t a0, uint32_t a1, uint32_t a2, uint32_t a3, uint64_t db, uint32_t acc) {
  asm volatile("{\n.reg .pred p;\nsetp.ne.b32 p, %53, 0;\n"
      "wgmma.mma_async.sync.aligned.m64n96k16.f32.bf16.bf16 "
      "{%0,%1,%2,%3,%4,%5,%6,%7,%8,%9,%10,%11,%12,%13,%14,%15,"
      "%16,%17,%18,%19,%20,%21,%22,%23,%24,%25,%26,%27,%28,%29,%30,%31,"
      "%32,%33,%34,%35,%36,%37,%38,%39,%40,%41,%42,%43,%44,%45,%46,%47}, "
      "{%48,%49,%50,%51}, %52, p, 1, 1, 1;\n}\n"
      : "+f"(d[0]), "+f"(d[1]), "+f"(d[2]), "+f"(d[3]), "+f"(d[4]), "+f"(d[5]), "+f"(d[6]), "+f"(d[7]),
        "+f"(d[8]), "+f"(d[9]), "+f"(d[10]), "+f"(d[11]), "+f"(d[12]), "+f"(d[13]), "+f"(d[14]), "+f"(d[15]),
        "+f"(d[16]), "+f"(d[17]), "+f"(d[18]), "+f"(d[19]), "+f"(d[20]), "+f"(d[21]), "+f"(d[22]), "+f"(d[23]),
        "+f"(d[24]), "+f"(d[25]), "+f"(d[26]), "+f"(d[27]), "+f"(d[28]), "+f"(d[29]), "+f"(d[30]), "+f"(d[31]),
        "+f"(d[32]), "+f"(d[33]), "+f"(d[34]), "+f"(d[35]), "+f"(d[36]), "+f"(d[37]), "+f"(d[38]), "+f"(d[39]),
        "+f"(d[40]), "+f"(d[41]), "+f"(d[42]), "+f"(d[43]), "+f"(d[44]), "+f"(d[45]), "+f"(d[46]), "+f"(d[47])
      : "r"(a0), "r"(a1), "r"(a2), "r"(a3), "l"(db), "r"(acc));
}
__device__ __forceinline__ void wgmma_n64_a(float (&d)[32], uint32_t a0, uint32_t a1, uint32_t a2, uint32_t a3, uint64_t db) {
  asm volatile("{\n.reg .pred p;\nsetp.ne.b32 p, 1, 0;\n"
      "wgmma.mma_async.sync.aligned.m64n64k16.f32.bf16.bf16 "
      "{%0,%1,%2,%3,%4,%5,%6,%7,%8,%9,%10,%11,%12,%13,%14,%15,"
      "%16,%17,%18,%19,%20,%21,%22,%23,%24,%25,%26,%27,%28,%29,%30,%31}, "
      "{%32,%33,%34,%35}, %36, p, 1, 1, 0;\n}\n"
      : "+f"(d[0]), "+f"(d[1]), "+f"(d[2]), "+f"(d[3]), "+f"(d[4]), "+f"(d[5]), "+f"(d[6]), "+f"(d[7]),
        "+f"(d[8]), "+f"(d[9]), "+f"(d[10]), "+f"(d[11]), "+f"(d[12]), "+f"(d[13]), "+f"(d[14]), "+f"(d[15]),
        "+f"(d[16]), "+f"(d[17]), "+f"(d[18]), "+f"(d[19]), "+f"(d[20]), "+f"(d[21]), "+f"(d[22]), "+f"(d[23]),
        "+f"(d[24]), "+f"(d[25]), "+f"(d[26]), "+f"(d[27]), "+f"(d[28]), "+f"(d[29]), "+f"(d[30]), "+f"(d[31])
      : "r"(a0), "r"(a1), "r"(a2), "r"(a3), "l"(db));
}
__device__ __forceinline__ void wgmma_n64_z(float (&d)[32], uint32_t a0, uint32_t a1, uint32_t a2, uint32_t a3, uint64_t db) {
  asm volatile("{\n.reg .pred p;\nsetp.ne.b32 p, 0, 0;\n"
      "wgmma.mma_async.sync.aligned.m64n64k16.f32.bf16.bf16 "
      "{%0,%1,%2,%3,%4,%5,%6,%7,%8,%9,%10,%11,%12,%13,%14,%15,"
      "%16,%17,%18,%19,%20,%21,%22,%23,%24,%25,%26,%27,%28,%29,%30,%31}, "
      "{%32,%33,%34,%35}, %36, p, 1, 1, 0;\n}\n"
      : "=f"(d[0]), "=f"(d[1]), "=f"(d[2]), "=f"(d[3]), "=f"(d[4]), "=f"(d[5]), "=f"(d[6]), "=f"(d[7]),
        "=f"(d[8]), "=f"(d[9]), "=f"(d[10]), "=f"(d[11]), "=f"(d[12]), "=f"(d[13]), "=f"(d[14]), "=f"(d[15]),
        "=f"(d[16]), "=f"(d[17]), "=f"(d[18]), "=f"(d[19]), "=f"(d[20]), "=f"(d[21]), "=f"(d[22]), "=f"(d[23]),
        "=f"(d[24]), "=f"(d[25]), "=f"(d[26]), "=f"(d[27]), "=f"(d[28]), "=f"(d[29]), "=f"(d[30]), "=f"(d[31])
      : "r"(a0), "r"(a1), "r"(a2), "r"(a3), "l"(db));
}

template <uint32_t OFF, uint32_t LBO>
__device__ __forceinline__ uint64_t desc_at(uint64_t base) {
  return base + (uint64_t)((OFF >> 4) + ((LBO >> 4) << 16));
}
template <uint32_t SBO, uint32_t SWIZZLE = 0>
__device__ __forceinline__ uint64_t desc_base(uint32_t addr4) {
  return ((uint64_t)SWIZZLE << 62) | ((uint64_t)(SBO >> 4) << 32) | (uint64_t)addr4;
}
__device__ __forceinline__ uint64_t pin(uint64_t v) {
  asm volatile("" : "+l"(v));
  return v;
}
template <int I> struct IC { static constexpr int v = I; };
template <int N, class F> __device__ __forceinline__ void static_for(F&& f) {
  if constexpr (N > 0) { static_for<N - 1>(f); f(IC<N - 1>{}); }
}

__device__ __forceinline__ void quad_origin(int win, int w, bool valid, int& row, int& col2) {
  col2 = (4 * (win & 63) + 2 + 2 * (w & 1)) & (IMG / 2 - 1);
  row = (8 * (win >> 6) + 4 + 4 * (w >> 1)) & (IMG - 1);
  if (!valid) row = IMG;
}
__device__ __forceinline__ void load_tile(uint32_t dst, int warp, int win, bool valid, uint32_t xbar, const CUtensorMap* tm_x) {
  int row, col2;
  quad_origin(win, warp, valid, row, col2);
  if (elect_one()) {
    mbar_expect_tx(xbar, 6144);
    tma_load5(dst, tm_x, row, col2, xbar);
  }
}
template <int S>
__device__ __forceinline__ void read_x(uint32_t (&xa)[48], const uint32_t (&xaddr)[4]) {
  ldmatrix_x4(xaddr[S & 3] + (S >> 2) * 2048, xa[4 * S], xa[4 * S + 1], xa[4 * S + 2], xa[4 * S + 3]);
}
__device__ __forceinline__ void reads_done(uint32_t last, uint32_t dummy_addr) {
  asm volatile("{\n.reg .pred p;\nsetp.eq.u32 p, %0, 0x7fc1fc17;\n@p st.shared.u32 [%1], %0;\n}\n" ::"r"(last), "r"(dummy_addr) : "memory");
}
template <int P>
__device__ __forceinline__ void store_chunk(uint32_t addr, float (&d)[48]) {
  stmatrix_x4(addr, pack_bf16(d[8 * P + 0], d[8 * P + 1]), pack_bf16(d[8 * P + 2], d[8 * P + 3]),
              pack_bf16(d[8 * P + 4], d[8 * P + 5]), pack_bf16(d[8 * P + 6], d[8 * P + 7]));
}
constexpr int IDLE = -100;
template <uint32_t WOFF, int H, bool TIED, class F>
__device__ __forceinline__ void gemm_phase(float (&run)[48], uint32_t (&x)[48], uint64_t w4, uint32_t rzero, F&& after) {
  wg_fence();
  static_for<12>([&](auto I) {
    constexpr int s = decltype(I)::v;
    const uint64_t d = desc_at<WOFF + (s / 6) * W_HALF + (s % 6) * 1024, 6144>(pin(w4));
    if constexpr (s == 0 && TIED) wgmma_n96_p(run, x[0], x[1], x[2], x[3], d, rzero);
    else if constexpr (s == 0) wgmma_n96_z(run, x[0], x[1], x[2], x[3], d);
    else wgmma_n96_a(run, x[4 * s], x[4 * s + 1], x[4 * s + 2], x[4 * s + 3], d);
    if constexpr (s == H - 1 || s == 11) wg_commit();
    if constexpr (s == H - 1) { after(IC<IDLE>{}); wg_wait<1>(); }
    after(I);
  });
}
template <int H>
__device__ __forceinline__ void issue_s(float (&s)[32], uint32_t (&q)[24], uint64_t k4_) {
  const uint64_t k4 = pin(k4_);
  static_for<3>([&](auto I) {
    constexpr int k = decltype(I)::v, i = 12 * H + 4 * k;
    const uint64_t d = desc_at<OFF_K + H * 768 + k * 256, 128>(k4);
    if constexpr (k == 0) wgmma_n64_z(s, q[i], q[i + 1], q[i + 2], q[i + 3], d);
    else wgmma_n64_a(s, q[i], q[i + 1], q[i + 2], q[i + 3], d);
  });
  wg_commit();
}
__device__ __forceinline__ const uint8_t* offset_ptr(const uint8_t* base, uint32_t off) {
  const uint8_t* r;
  asm volatile("{\n.reg .u64 o;\ncvt.u64.u32 o, %2;\nadd.u64 %0, %1, o;\n}\n" : "=l"(r) : "l"(base), "r"(off));
  return r;
}
struct MaskRows { uint4 a, b, c, d; };
__device__ __forceinline__ MaskRows mask_load(const uint8_t* mp) {
  MaskRows r;
  r.a = ldg128(mp); r.b = ldg128(mp + 1024); r.c = ldg128(mp + 2048); r.d = ldg128(mp + 3072);
  return r;
}
__device__ __forceinline__ void pin_rows(MaskRows& r) {
  asm volatile("" : "+r"(r.a.x), "+r"(r.a.y), "+r"(r.a.z), "+r"(r.a.w), "+r"(r.b.x), "+r"(r.b.y), "+r"(r.b.z), "+r"(r.b.w),
                    "+r"(r.c.x), "+r"(r.c.y), "+r"(r.c.z), "+r"(r.c.w), "+r"(r.d.x), "+r"(r.d.y), "+r"(r.d.z), "+r"(r.d.w)::"memory");
}
__device__ __forceinline__ uint32_t mask_or(const MaskRows& r) {
  return (r.a.x | r.a.y | r.a.z | r.a.w) | (r.b.x | r.b.y | r.b.z | r.b.w) | (r.c.x | r.c.y | r.c.z | r.c.w) | (r.d.x | r.d.y | r.d.z | r.d.w);
}
__device__ __forceinline__ void add_mask(float (&s0)[32], float (&s1)[32], const uint4 (&m)[4]) {
#pragma unroll
  for (int t = 0; t < 2; t++) {
#pragma unroll
    for (int b = 0; b < 8; b++) {
      const uint4 u = m[2 * t + (b >> 2)];
      const uint32_t v = (b & 3) == 0 ? u.x : (b & 3) == 1 ? u.y : (b & 3) == 2 ? u.z : u.w;
      const int i = 4 * b + 2 * t;
      s0[i] = fmaf(bf_lo(v), LOG2E, s0[i]); s0[i + 1] = fmaf(bf_hi(v), LOG2E, s0[i + 1]);
      s1[i] = fmaf(bf_lo(v), LOG2E, s1[i]); s1[i + 1] = fmaf(bf_hi(v), LOG2E, s1[i + 1]);
    }
  }
}
__device__ __forceinline__ void subtract_row_max(float (&s)[32]) {
#pragma unroll
  for (int t = 0; t < 2; t++) {
    float x = -INFINITY;
#pragma unroll
    for (int b = 0; b < 8; b++) x = fmaxf(x, fmaxf(s[4 * b + 2 * t], s[4 * b + 2 * t + 1]));
    x = fmaxf(x, __shfl_xor_sync(0xffffffffu, x, 1));
    x = fmaxf(x, __shfl_xor_sync(0xffffffffu, x, 2));
#pragma unroll
    for (int b = 0; b < 8; b++) { s[4 * b + 2 * t] -= x; s[4 * b + 2 * t + 1] -= x; }
  }
}
template <int I0, int I1>
__device__ __forceinline__ void exp_pairs(float (&s)[32]) {
#pragma unroll
  for (int i = 2 * I0; i < 2 * I1; i++) {
    asm volatile("" : "+f"(s[i])::"memory");
    s[i] = ex2(s[i]);
    asm volatile("" : "+f"(s[i])::"memory");
  }
}
template <int I0, int I1>
__device__ __forceinline__ void pack_pairs(float (&s)[32], const uint32_t (&eb)[16], uint32_t (&p)[16], uint32_t (&z)[6]) {
#pragma unroll
  for (int i = I0; i < I1; i++) {
    asm volatile("" : "+f"(s[2 * i]), "+f"(s[2 * i + 1])::"memory");
    p[i] = hmul2(pack_bf16(s[2 * i], s[2 * i + 1]), eb[i]);
    asm volatile("" : "+r"(p[i])::"memory");
    const int b = i >> 1, t = i & 1;
    if (b & 1) {
      uint32_t v = hadd2(p[i - 2], p[i]);
      if (b & 2) v = hadd2(z[4 + t], v);
      if (b == 7) v = hadd2(z[2 + t], v);
      uint32_t& dst = z[(b == 7 ? 0 : (b & 2) ? 2 : 4) + t];
      dst = v;
      asm volatile("" : "+r"(dst)::"memory");
    }
  }
}
struct RowSums {
  uint32_t a, b, c, d;
  __device__ __forceinline__ void start(const uint32_t (&z)[6]) {
    a = hadd2(__byte_perm(z[0], z[1], 0x5410), __byte_perm(z[0], z[1], 0x7632));
    b = __shfl_xor_sync(0xffffffffu, a, 1);
    c = __shfl_xor_sync(0xffffffffu, a, 2);
    d = __shfl_xor_sync(0xffffffffu, a, 3);
  }
  __device__ __forceinline__ uint32_t finish() {
    asm volatile("" : "+r"(a), "+r"(b), "+r"(c), "+r"(d)::"memory");
    const uint32_t x = hadd2(a, b), y = hadd2(c, d);
    return pack_bf16(rcp_approx(bf_lo(x) + bf_lo(y)), rcp_approx(bf_hi(x) + bf_hi(y)));
  }
};
template <int H>
__device__ __forceinline__ void issue_pv(float (&oacc)[24], uint32_t (&p)[16], uint64_t v4_) {
  const uint64_t v4 = pin(v4_);
  static_for<4>([&](auto I) {
    constexpr int k = decltype(I)::v;
    const uint64_t d = desc_at<OFF_V + H * 6144 + k * 256, 128>(v4);
    if constexpr (k == 0) wgmma_n48_z(oacc, p[0], p[1], p[2], p[3], d);
    else wgmma_n48_a(oacc, p[4 * k], p[4 * k + 1], p[4 * k + 2], p[4 * k + 3], d);
  });
  wg_commit();
}
constexpr uint32_t BAD_SUM = 0xE000E000u;
template <int H>
__device__ __forceinline__ uint32_t normalize(float (&oacc)[24], uint32_t r, uint32_t (&o)[48]) {
  const uint32_t ra = dup_lo(r), rb = dup_hi(r);
#pragma unroll
  for (int k = 0; k < 12; k++) o[12 * H + k] = hmul2(pack_bf16(oacc[2 * k], oacc[2 * k + 1]), (k & 1) ? rb : ra);
  return r - 0x2F802F80u;
}

struct Params {
  const __nv_bfloat16 *x, *wqkv, *wo, *rpb;
  const int* rp_idx;
  const __nv_bfloat16* mask;
  __nv_bfloat16* out;
  int nk_min, nk_rem, wstride, wskip, zero;
};
__device__ __forceinline__ float round_bf16(float v) { return __bfloat162float(__float2bfloat16(v)); }
__device__ __forceinline__ void redo_window(const Params& P, float* sm, int win, int rank) {
  float* xt = sm;
  float* qkv = sm + 192 * 64;
  const int tid = threadIdx.x;
  auto pixel = [&](int n) { return (size_t)(((8 * (win >> 6) + (n >> 3) + 4) & (IMG - 1)) * IMG + ((8 * (win & 63) + (n & 7) + 4) & (IMG - 1))) * CH; };
  auto gemm = [&](const __nv_bfloat16* w, int ldw, int ncols, auto&& put) {
    for (int e = tid; e < 4 * ncols; e += THREADS) {
      const int g = e / ncols, d = e - g * ncols;
      float acc[16];
#pragma unroll
      for (int i = 0; i < 16; i++) acc[i] = 0.f;
      for (int c = 0; c < CH; c++) {
        const float wv = __bfloat162float(w[c * ldw + d]);
#pragma unroll
        for (int i = 0; i < 16; i++) acc[i] = fmaf(xt[c * 64 + 16 * g + i], wv, acc[i]);
      }
#pragma unroll
      for (int i = 0; i < 16; i++) put(16 * g + i, d, acc[i]);
    }
  };
  __syncthreads();
  for (int e = tid; e < 64 * CH; e += THREADS) xt[(e % CH) * 64 + e / CH] = __bfloat162float(P.x[pixel(e / CH) + e % CH]);
  __syncthreads();
  gemm(P.wqkv, 3 * CH, 3 * CH, [&](int n, int d, float v) { qkv[n * 577 + d] = round_bf16(v); });
  __syncthreads();
  {
    const int n = tid & 63, h = tid >> 6;
    auto logit = [&](int m) {
      float s = 0.f;
      for (int d = 0; d < 48; d++) s = fmaf(qkv[n * 577 + 48 * h + d], qkv[m * 577 + CH + 48 * h + d], s);
      return s * SCALE + __bfloat162float(P.rpb[P.rp_idx[n * 64 + m] * 4 + h]) + __bfloat162float(P.mask[(size_t)win * 4096 + n * 64 + m]);
    };
    float mx = -INFINITY, sum = 0.f, o[48];
    for (int m = 0; m < 64; m++) mx = fmaxf(mx, logit(m));
#pragma unroll
    for (int d = 0; d < 48; d++) o[d] = 0.f;
    for (int m = 0; m < 64; m++) {
      const float p = expf(logit(m) - mx);
      sum += p;
#pragma unroll
      for (int d = 0; d < 48; d++) o[d] = fmaf(p, qkv[m * 577 + 2 * CH + 48 * h + d], o[d]);
    }
#pragma unroll
    for (int d = 0; d < 48; d++) xt[(48 * h + d) * 64 + n] = round_bf16(o[d] / sum);
  }
  __syncthreads();
  gemm(P.wo + 96 * rank, CH, 96, [&](int n, int d, float v) { P.out[pixel(n) + 96 * rank + d] = __float2bfloat16(v); });
}

#define HO 6
#define HQ 6
#define HV 6
#define E0 5
#define E1 15
#define ET 3
#define XSL "11110022220000"
#define XD 11
#define MS 8
#define KF 2
#define LF 9
#define NB 4
#define LAG 2
#define RA 0
#define QP 0
#define X1P 1
#define VP 2
#define X2P 4
#define K1W 1
#define HF 6
#define OF 5
__host__ __device__ constexpr int g0(int r) { return r < 5 ? 3 * r : 16; }
__host__ __device__ constexpr int g1(int r) { return NB + (16 - NB) * r / 4; }
__host__ __device__ constexpr int xslot(int i) { return XSL[i] - '0'; }
__host__ __device__ constexpr int xbase(int i) { int b = 0; for (int q = 0; q < i; q++) b += xslot(q); return b; }
__host__ __device__ constexpr int xlast() { int l = 0; for (int q = 0; q < 14; q++) if (xslot(q)) l = q; return l; }
static_assert(xbase(14) == 12 && XD >= xlast(), "X schedule");

__global__ void __cluster_dims__(2, 1, 1) __launch_bounds__(THREADS, 1)
swin_attn_kernel(const __grid_constant__ CUtensorMap tm_x, const __grid_constant__ CUtensorMap tm_o, const __grid_constant__ CUtensorMap tm_w,
                 const __grid_constant__ CUtensorMap tm_wo, const __grid_constant__ Params P) {
  extern __shared__ __align__(1024) uint8_t smem_raw[];
  const uint32_t sbase = smem_u32(smem_raw);
  const int tid = threadIdx.x;
  const int wid = uniform(tid >> 5);
  const int j = wid >> 2, warp = wid & 3;
  const uint32_t lane = tid & 31;
  uint32_t rank;
  asm("mov.u32 %0, %%cluster_ctarank;" : "=r"(rank));
  auto load_w = [&](int part) {
#pragma unroll
    for (int h = 0; h < 2; h++) {
      const uint32_t b = sbase + B_W + (part == 0 && h == 0 ? 32 : 8 * part);
      if (part == 0 || h == 0) mbar_expect_tx(b, part == 0 ? W_HALF : W_PART);
      if (part < 3) tma_load3(sbase + OFF_W + part * W_PART + h * W_HALF, &tm_w, 96 * h, (part == 0 ? 6 : part == 1 ? 0 : 12) + 3 * rank, b);
      else tma_load3(sbase + WO + h * W_HALF, &tm_wo, 96 * (rank ^ h), 3 * rank, b);
    }
  };
  uint32_t tab[4] = {0, 0, 0, 0};
  if ((wid >> 1) == 2) {
    const uint32_t* tp = reinterpret_cast<const uint32_t*>(P.rpb) + 2 * (tid - 128) + rank;
#pragma unroll
    for (int i = 0; i < 4; i++)
      if (i < 3 || tid < 128 + 33) asm volatile("ld.global.nc.u32 %0, [%1];" : "=r"(tab[i]) : "l"(tp + 128 * i) : "memory");
    if (elect_one()) {
      const uint32_t b = sbase + OFF_BAR + 128 * (wid & 1);
#pragma unroll
      for (uint32_t o = B_TOKEN; o <= B_LFREE; o += 8) mbar_init(b + o, 4);
      if (wid == 4) {
        mbar_arrive4(b + B_TOKEN);
        mbar_arrive4(b + B_KFREE);
        mbar_arrive4(b + B_VFREE);
      } else {
        mbar_init(sbase + B_DONE, 8);
      }
      asm volatile("fence.mbarrier_init.release.cluster;" ::: "memory");
    }
  } else {
    if (wid == 7 && lane < 18 && blockIdx.x < 128)
      asm volatile("prefetch.global.L2 [%0];" ::"l"((blockIdx.x < 96 ? reinterpret_cast<const uint8_t*>(P.wqkv) + blockIdx.x * 2304 : reinterpret_cast<const uint8_t*>(P.wo) + (blockIdx.x - 96) * 2304) + lane * 128) : "memory");
    if (elect_one()) {
      const uint32_t b0 = sbase + (j == 0 ? OFF_BAR + B_XFULL + 8 * warp : wid == 6 ? B_IDX : B_W);
      const uint32_t b1 = sbase + (j == 0 ? OFF_BAR + 128 + B_XFULL + 8 * warp : wid == 6 ? B_W + 8 : B_W + 32);
      const uint32_t b2 = sbase + (j == 0 ? OFF_BAR + 128 + B_X1 + 8 * warp : wid == 6 ? B_W + 16 : B_W + 24);
      mbar_init(b0, 1);
      mbar_init(b1, 1);
      mbar_init(b2, 1);
      if (j == 0) mbar_arrive(b1);
      fence_async_proxy();
      if (wid == 6) {
        mbar_expect_tx(sbase + B_IDX, 16384);
        bulk_load(sbase + WO, P.rp_idx, 16384, sbase + B_IDX);
      }
    }
  }
  __syncwarp();
  const int cluster = blockIdx.x >> 1;
  const int nk = uniform(P.nk_min + (cluster < P.nk_rem) + (tid >> 10));
  const bool special = P.wskip != 0;
  const int nspecial = (!special || cluster < 4) ? 0 : cluster < 7 ? 3 : 2;
  const int wbase = special ? cluster - 127 : cluster;
  auto inner = [&](int a) { return a + (int)((uint32_t)(a * P.wskip) >> 20); };
  auto window = [&](int k) { return inner(wbase + k * P.wstride); };
  auto window_any = [&](int k) {
    const int v = k == 2 ? cluster - 4 : k == 3 ? cluster + 61 : 58 + cluster, b = v < 64 ? 64 * v + 63 : 3968 + v;
    const int u = k == 0 ? cluster : k == 1 ? (cluster < 4 ? 66 : 63) + cluster : 121 + 4 * k + cluster;
    return (k >= 4 || !special) ? window(k) : k < 4 - nspecial ? inner(u) : b;
  };
  int win = window_any(j);
  const uint8_t* mask_b = reinterpret_cast<const uint8_t*>(P.mask);
  const uint32_t quad_row = 32 * (warp >> 1) + 4 * (warp & 1);
  const uint8_t* mask_q0 = mask_b + quad_row * 128;
  MaskRows mr;
  if (j == 0) {
    mr = mask_load(mask_q0 + (size_t)win * 8192 + lane * 16);
    load_tile(sbase + OFF_X + warp * 6144, warp, win, true, sbase + OFF_BAR + B_XFULL + 8 * warp, &tm_x);
  }
  if (wid == 7 && elect_one()) load_w(0);
  if (sbase & 1023) __trap();
  const uint32_t bar = uniform(smem_u32(smem_raw) + OFF_BAR + (tid & 128)), bar_o = uniform(smem_u32(smem_raw) + OFF_BAR + ((tid & 128) ^ 128));
  const uint32_t xbar = uniform(smem_u32(smem_raw) + OFF_BAR + (tid & 128) + B_XFULL + 8 * ((tid >> 5) & 3));
  const uint32_t xbar_o = uniform(smem_u32(smem_raw) + OFF_BAR + ((tid & 128) ^ 128) + B_XFULL + 8 * ((tid >> 5) & 3));
  const uint32_t xdst = uniform(smem_u32(smem_raw) + OFF_X + ((tid >> 5) & 3) * 6144);
  const uint32_t x1off = j == 0 ? 0 : warp < 2 ? OFF_L + 12288 : WO + 16384 - 12288;
  auto loads = [&](int step) {
    if (j == 1) {
      if (QP == step && warp == 0 && elect_one()) load_w(1);
      if (X1P == step) load_tile(xdst + x1off, warp, win, true, xbar + B_X1, &tm_x);
      if (VP == step && warp == 2 && elect_one()) load_w(2);
      if (X2P == step) load_tile(xdst, warp, window_any(2), 2 < nk, xbar_o, &tm_x);
    }
  };
  asm volatile("st.shared.u32 [%0], %1;" ::"r"(sbase + OFF_FAIL + 4 * tid), "r"(0) : "memory");
  bool big = false;
  if ((wid >> 1) == 2) {
#pragma unroll
    for (int i = 0; i < 4; i++) {
      const float b0 = bf_lo(tab[i]) * LOG2E, b1 = bf_hi(tab[i]) * LOG2E;
      asm volatile("st.shared.u32 [%0], %1;" ::"r"(sbase + OFF_TAB + 4 * (tid - 128) + 256 * i), "r"(pack_bf16(ex2(b0), ex2(b1))) : "memory");
      big = big || !(fabsf(b0) <= 60.f && fabsf(b1) <= 60.f);
    }
  }
  uint32_t force = __syncthreads_or(big) ? BAD_SUM : 0u;
  asm volatile("barrier.cluster.arrive.relaxed.aligned;" ::: "memory");
  loads(0);
  const uint32_t sb_a = uniform((sbase & 0x3FFFF) >> 4);
  const uint64_t w4 = desc_base<512, 2>(sb_a), k4 = desc_base<UB>(sb_a), v4 = desc_base<1024>(sb_a);
  const uint32_t blk = 2 * warp + ((lane >> 3) & 1);
  uint32_t stk = sbase + OFF_K + blk * UB + (lane >> 4) * 128 + (lane & 7) * 16;
  uint32_t stv = sbase + OFF_V + (lane >> 4) * 1024 + blk * 128 + (lane & 7) * 16;
  uint32_t xaddr0 = xdst + (lane & 15) * 128 + (((lane >> 4) ^ (lane & 7)) << 4);
  const uint32_t peer = rank ^ 1;
  const uint32_t area = uniform(smem_u32(smem_raw) + OFF_L + (tid >> 5) * 3072);
  const uint32_t r_bar = uniform(mapa(bar, peer)), r_area = uniform(mapa(area, peer));
  uint32_t l16 = lane * 16;
  uint32_t out_res = area + (lane & 15) * 64 + (((lane >> 4) ^ ((lane >> 1) & 3)) << 4);
  const uint32_t rzero = uniform(P.zero + (tid >> 10));
  const uint64_t mq = reinterpret_cast<uint64_t>(mask_b) + (32 * ((tid >> 6) & 1) + 4 * ((tid >> 5) & 1)) * 128;
  const uint8_t* mask_q = reinterpret_cast<const uint8_t*>(((uint64_t)uniform((uint32_t)(mq >> 32)) << 32) | uniform((uint32_t)mq));

  sched_barrier(stk, rzero); sched_barrier(stv, rzero); sched_barrier(xaddr0, rzero); sched_barrier(out_res, rzero); sched_barrier(l16, rzero);
  uint32_t xa[48], oo[48], eb0[16], eb1[16];
  auto fetch = [&](auto H) {
    constexpr int o = 24 + 12 * decltype(H)::v;
    const uint32_t addr = area + l16 + 1536 * decltype(H)::v;
    const uint4 x = lds128v(addr), y = lds128v(addr + 512), z = lds128v(addr + 1024);
    oo[o + 0] = x.x; oo[o + 1] = x.y; oo[o + 2] = x.z; oo[o + 3] = x.w; oo[o + 4] = y.x; oo[o + 5] = y.y; oo[o + 6] = y.z; oo[o + 7] = y.w;
    oo[o + 8] = z.x; oo[o + 9] = z.y; oo[o + 10] = z.z; oo[o + 11] = z.w;
  };
  auto store_out = [&](auto PP, float (&d)[48]) {
    constexpr int p = decltype(PP)::v;
    store_chunk<p>(((p & 1) ? (out_res ^ 32) : out_res) + (p >> 1) * 1024, d);
  };
  uint64_t streaming;
  asm("createpolicy.fractional.L2::evict_first.b64 %0, 1.0;" : "=l"(streaming));
  auto send_out = [&](int w, bool valid) {
    int row, col2;
    quad_origin(w, warp, valid, row, col2);
    if (elect_one()) tma_store5(&tm_o, row, col2, 3 * rank, area, streaming);
    asm volatile("cp.async.bulk.commit_group;" ::: "memory");
  };
  auto prefetch_mask = [&](int w) {
    if (elect_one()) prefetch_l2(mask_b + (size_t)w * 8192 + (rank * 4 + warp) * 1024, 1024);
  };
  auto prefetch_x = [&](int w) {
    const int row = (8 * (w >> 6) + 4 + 4 * rank + warp) & (IMG - 1), col = 8 * (w & 63) + 4;
    if (elect_one()) prefetch_l2(reinterpret_cast<const uint8_t*>(P.x) + (size_t)(row * IMG + col) * (CH * 2), (w & 63) == 63 ? 4 * CH * 2 : 8 * CH * 2);
  };

  auto first_x = [&]() {
    uint32_t xaddr[4], all = ~0u;
#pragma unroll
    for (int q = 0; q < 4; q++) xaddr[q] = (xaddr0 + x1off) ^ (q << 5);
    mbar_wait(xbar + j * B_X1, 0);
    static_for<12>([&](auto I) { read_x<decltype(I)::v>(xa, xaddr); all &= xa[4 * decltype(I)::v + 3]; });
    reads_done(all, sbase + OFF_DUMMY);
  };
  auto gather = [&]() {
    const uint32_t odd = (l16 >> 6) & 1;
    const uint32_t ia = sbase + WO + (quad_row + 8 * (l16 >> 7) + odd) * 256 + (l16 & 0x30) * 2;
    mbar_wait(sbase + B_IDX, 0);
#pragma unroll
    for (int i = 0; i < 4; i++) {
      const int t = i >> 1, b = 4 * (i & 1);
      const uint4 u0 = lds128(ia + t * 512 + (i & 1) * 128 + odd * 16), u1 = lds128(ia + t * 512 + (i & 1) * 128 + 16 - odd * 16);
      const uint32_t id[8] = {u0.x, u0.y, u0.z, u0.w, u1.x, u1.y, u1.z, u1.w};
      uint32_t v[8];
#pragma unroll
      for (int q = 0; q < 8; q++) v[q] = lds32(sbase + OFF_TAB + 4 * id[q]);
#pragma unroll
      for (int q = 0; q < 4; q++) {
        const uint32_t x = odd ? v[(2 * q) ^ 4] : v[2 * q], y = odd ? v[(2 * q + 1) ^ 4] : v[2 * q + 1];
        eb0[2 * (b + q) + t] = __byte_perm(x, y, 0x5410);
        eb1[2 * (b + q) + t] = __byte_perm(x, y, 0x7632);
      }
    }
  };
  gather();
#pragma unroll
  for (int i = 0; i < 16; i += 4) {
    asm volatile("{\n.reg .pred p;\nsetp.ne.u32 p, %4, 0;\n@p ld.shared.v4.u32 {%0,%1,%2,%3}, [%4];\n}\n" : "+r"(eb0[i]), "+r"(eb0[i + 1]), "+r"(eb0[i + 2]), "+r"(eb0[i + 3]) : "r"(rzero));
    asm volatile("{\n.reg .pred p;\nsetp.ne.u32 p, %4, 0;\n@p ld.shared.v4.u32 {%0,%1,%2,%3}, [%4];\n}\n" : "+r"(eb1[i]), "+r"(eb1[i + 1]), "+r"(eb1[i + 2]), "+r"(eb1[i + 3]) : "r"(rzero));
  }
  loads(1);
#pragma unroll
  for (int h = 0; h < 2; h++) {
    constexpr uint32_t HI = 0x3E553E55u, LO = 0x396E396Eu;
    const uint32_t a = sbase + WK + h * 16384 + tid * 16;
    uint4 v[5];
    if (h == 0) mbar_wait(sbase + B_W + 32, 0);
    else mbar_wait(sbase + B_W, 0);
#pragma unroll
    for (int i = 0; i < 4 + h; i++) v[i] = lds128(a + i * 4096);
    loads(2 + h);
#pragma unroll
    for (int i = 0; i < 4 + h; i++)
      sts128(a + i * 4096, make_uint4(hfma2(v[i].x, HI, hmul2(v[i].x, LO)), hfma2(v[i].y, HI, hmul2(v[i].y, LO)),
                                      hfma2(v[i].z, HI, hmul2(v[i].z, LO)), hfma2(v[i].w, HI, hmul2(v[i].w, LO))));
  }
  fence_async_proxy();
  if (j == 0) first_x();
  bool masked = false;
  if (j == 0) {
    pin_rows(mr);
    masked = __any_sync(0xffffffffu, mask_or(mr) != 0);
  }
  __syncthreads();
  if (j == 1) {
    loads(4);
    mr = mask_load(mask_q0 + (size_t)win * 8192 + lane * 16);
    first_x();
    loads(5);
    wg_barrier(1);
    if (warp == 3 && elect_one()) load_w(3);
    if (2 < nk) prefetch_mask(window_any(2));
    if (3 < nk) {
      prefetch_x(window_any(3));
      prefetch_mask(window_any(3));
    }
    pin_rows(mr);
    masked = __any_sync(0xffffffffu, mask_or(mr) != 0);
  }

  uint32_t par = 0;
  auto sched = [&]() { sched_barrier(force, rzero); };
  int k = j, wprev = win, wnext = window_any(j + 2), wx = window_any(j + 3);
#pragma unroll
  for (int i = 0; i < 24; i++) oo[i] = 0;
  for (;;) {
    float ca[48], cb[48], s0[32], s1[32];
    uint32_t qf[24];
    const int wnn = window(k + 4);
    bool ex0, ex1, kfree;
    fence_regs(xa);
    if (k == j) {
      if (K1W == 1 && j == 1) mbar_wait(bar + B_TOKEN, 0);
      gemm_phase<WK, 0, false>(ca, xa, w4, rzero, [&](auto) {});
      cluster_wait();
      if (K1W == 2 && j == 1) mbar_wait(bar + B_TOKEN, 0);
      mbar_wait(sbase + B_W + 8, 0);
      gemm_phase<WQ, HF, false>(cb, xa, w4, rzero, [&](auto I) {
        constexpr int s = decltype(I)::v, p = s - (HF - 1);
        if constexpr (p == 0) { fence_regs(ca); mbar_wait(bar + B_KFREE, 0); }
        if constexpr (p >= 0 && p < 6) store_chunk<(p >= 0 && p < 6) ? p : 0>(stk + p * 256, ca);
      });
      mbar_wait(sbase + B_W + 16, 0);
      if (j == 1) mbar_wait(sbase + B_W + 24, 0);
    } else {
      auto exchange = [&](auto G) {
        constexpr int g = decltype(G)::v;
        if constexpr (g == E0 - ET) ex0 = mbar_test(bar + B_EX0, par ^ 1);
        if constexpr (g == E1 - ET) ex1 = mbar_test(bar + B_EX1, par ^ 1);
        if constexpr (g == E0) { if (!ex0) mbar_wait(bar + B_EX0, par ^ 1); fetch(IC<0>{}); }
        if constexpr (g == E1) { if (!ex1) mbar_wait(bar + B_EX1, par ^ 1); fetch(IC<1>{}); }
      };
      gemm_phase<WK, 0, false>(cb, xa, w4, rzero, [&](auto I) { exchange(I); });
      gemm_phase<WO, HO, false>(ca, oo, w4, rzero, [&](auto I) {
        constexpr int s = decltype(I)::v, p = s - (HO - 1);
        if constexpr (p == -2) kfree = mbar_test(bar + B_KFREE, par);
        if constexpr (p == 0) { fence_regs(cb); if (!kfree) mbar_wait(bar + B_KFREE, par); }
        if constexpr (p >= 0 && p < 6) store_chunk<(p >= 0 && p < 6) ? p : 0>(stk + p * 256, cb);
        exchange(IC<12 + s>{});
        if constexpr (s == OF) wg_fence();
      });
      gemm_phase<WQ, HQ, false>(cb, xa, w4, rzero, [&](auto I) {
        constexpr int s = decltype(I)::v, p = s - (HQ - 1);
        if constexpr (p == 0) { fence_regs(ca); }
        if constexpr (p >= 0 && p < 6) store_out(IC<(p >= 0 && p < 6) ? p : 0>{}, ca);
      });
    }
    gemm_phase<WV, HV, true>(ca, xa, w4, rzero, [&](auto I) {
      constexpr int s = decltype(I)::v, p = s - (HV - 1);
      if constexpr (s == IDLE) {
        if (k + 4 < nk) {
          prefetch_mask(wnn);
          prefetch_x(wnn);
        }
        if (l16 == 0) {
          mbar_expect_tx(bar + B_EX0, 1536);
          mbar_expect_tx(bar + B_EX1, 1536);
        }
      }
      if constexpr (p == 0) { fence_regs(cb); }
      if constexpr (p >= 0 && p < 6) {
#pragma unroll
        for (int i = 4 * p; i < 4 * p + 4; i++) qf[i] = pack_bf16(cb[2 * i], cb[2 * i + 1]);
      }
    });
    fence_regs(qf);
    fence_async_proxy();
    wg_barrier(j);
    wg_fence();
    issue_s<0>(s0, qf, k4);
    const bool vfree = mbar_test(bar + B_VFREE, par), xfull = mbar_test(xbar, par ^ 1);
    issue_s<1>(s1, qf, k4);
    if (l16 == 0) mbar_arrive(bar_o + B_TOKEN);
    send_out(wprev, k != j);
    uint32_t xaddr[4];
#pragma unroll
    for (int q = 0; q < 4; q++) xaddr[q] = xaddr0 ^ (q << 5);
    auto side = [&](auto R) {
      constexpr int r = decltype(R)::v, c = xslot(r), b = xbase(r);
      if constexpr (r == KF) {
        wg_wait<0>();
        fence_regs(s1);
        fence_regs(qf);
        if (l16 == 0) mbar_arrive(bar_o + B_KFREE);
      }
      if constexpr (r == LF) {
        asm volatile("cp.async.bulk.wait_group.read 0;" ::: "memory");
        __syncwarp();
        if (l16 == 0) mbar_arrive_remote_relaxed(r_bar + B_LFREE);
      }
      if constexpr (b == 0 && c > 0) { if (!xfull) mbar_wait(xbar, par ^ 1); }
      if constexpr (r == MS) mr = mask_load(offset_ptr(mask_q + (size_t)(k + 2 < nk ? wnext : win) * 8192, l16));
      static_for<c>([&](auto J) { read_x<b + decltype(J)::v>(xa, xaddr); });
      if constexpr (r == XD) {
        uint32_t all = ~0u;
#pragma unroll
        for (int i = 12 - xslot(xlast()); i < 12; i++) all &= xa[4 * i + 3];
        reads_done(all, sbase + OFF_DUMMY);
        load_tile(xdst, warp, wx, k + 3 < nk, xbar_o, &tm_x);
      }
    };
    auto store_v = [&](auto PP) { store_chunk<decltype(PP)::v>(stv + decltype(PP)::v * 2048, ca); };
    float o0[24], o1[24];
    uint32_t p0[16], p1[16], z0[6], z1[6], r0, r1;
    RowSums l0, l1;
    if (!vfree) mbar_wait(bar + B_VFREE, par);
    wg_wait<2>();
    fence_regs(ca);
    fence_regs(xa);
    store_v(IC<0>{});
    side(IC<0>{});
    store_v(IC<1>{});
    wg_wait<1>();
    fence_regs(s0);
    static_for<5>([&](auto R) {
      constexpr int r = decltype(R)::v;
      side(IC<1 + r>{});
      if constexpr (r == 0) {
        if (masked) {
          uint32_t l = l16;
          asm volatile("" : "+r"(l));
          const uint8_t* mp = offset_ptr(mask_q + (size_t)win * 8192, (l & 0x180) * 8 + (l & 0x40) * 2 + (l & 0x30));
          wg_wait<0>();
          fence_regs(s0);
          fence_regs(s1);
          const uint4 m[4] = {ldg128(mp), ldg128(mp + 64), ldg128(mp + 256), ldg128(mp + 320)};
          add_mask(s0, s1, m);
          if (__any_sync(0xffffffffu, force != 0)) {
            subtract_row_max(s0);
            subtract_row_max(s1);
          }
        }
      }
      if constexpr (r < 4) store_v(IC<(r < 4 ? r + 2 : 0)>{});
      exp_pairs<g0(r), g0(r + 1)>(s0);
      pack_pairs<(g0(r) > LAG ? g0(r) - LAG : 0), g0(r + 1) - LAG>(s0, eb0, p0, z0);
      sched();
    });
    fence_async_proxy();
    exp_pairs<0, NB>(s1);
    pack_pairs<16 - LAG, 16>(s0, eb0, p0, z0);
    pack_pairs<0, (NB > LAG ? NB - LAG : 0)>(s1, eb1, p1, z1);
    l0.start(z0);
    sched();
    wg_barrier(j);
    side(IC<6>{});
    wg_fence();
    issue_pv<0>(o0, p0, v4);
    sched();
    static_for<4>([&](auto R) {
      constexpr int r = decltype(R)::v;
      if constexpr (r == RA) r0 = l0.finish();
      side(IC<7 + r>{});
      exp_pairs<g1(r), g1(r + 1)>(s1);
      pack_pairs<(g1(r) > LAG ? g1(r) - LAG : 0), (r < 3 ? g1(r + 1) - LAG : 16)>(s1, eb1, p1, z1);
      if (r < 3) sched();
    });
    wg_fence();
    issue_pv<1>(o1, p1, v4);
    sched();
    l1.start(z1);
    side(IC<11>{});
    wg_wait<1>();
    fence_regs(o0);
    fence_regs(p0);
    uint32_t bad = normalize<0>(o0, r0, oo);
    mbar_wait(bar + B_LFREE, par);
#pragma unroll
    for (int q = 0; q < 3; q++) st_async16(r_area + l16 + q * 512, oo[4 * q], oo[4 * q + 1], oo[4 * q + 2], oo[4 * q + 3], r_bar + B_EX0);
    sched();
    r1 = l1.finish();
    side(IC<12>{});
    wg_wait<0>();
    fence_regs(o1);
    fence_regs(p1);
    if (l16 == 0) mbar_arrive(bar_o + B_VFREE);
    bad = ((bad | normalize<1>(o1, r1, oo)) & BAD_SUM) | force;
#pragma unroll
    for (int q = 3; q < 6; q++) st_async16(r_area + l16 + q * 512, oo[4 * q], oo[4 * q + 1], oo[4 * q + 2], oo[4 * q + 3], r_bar + B_EX1);
    sched();
    side(IC<13>{});
    pin_rows(mr);
    masked = __any_sync(0xffffffffu, (mask_or(mr) | bad) != 0);
    if (masked && __any_sync(0xffffffffu, (bad & BAD_SUM) != 0)) {
      force |= 1;
      if ((l16 >> 4) == (uint32_t)(k >> 6)) asm volatile("red.shared.or.b32 [%0], %1;" ::"r"(sbase + OFF_FAIL + 512 * j + 128 * warp + (l16 >> 2)), "r"(1u << ((k >> 1) & 31)) : "memory");
    }
    wprev = win;
    win = wnext;
    wnext = wnn;
    wx = window(k + 5);
    k += 2;
    if (k >= nk) break;
    par ^= 1;
    mbar_wait(bar + B_TOKEN, par);
  }
  {
    const uint32_t a = sbase + OFF_FAIL + 512 * j + 128 * warp + (l16 >> 2);
    st_async4(mapa(a + 1024, peer), lds32(a), mapa(sbase + B_DONE, peer));
    __syncwarp();
    if (l16 == 0) mbar_expect_tx(sbase + B_DONE, 128);
  }
  {
    float ca[48];
    mbar_wait(sbase + B_W + 24, 0);
    gemm_phase<WO, 0, false>(ca, oo, w4, rzero, [&](auto I) {
      constexpr int s = decltype(I)::v;
      if constexpr (s == 5) { mbar_wait(bar + B_EX0, par); fetch(IC<0>{}); wg_fence(); }
      if constexpr (s == 8) { mbar_wait(bar + B_EX1, par); fetch(IC<1>{}); wg_fence(); }
    });
    wg_wait<0>();
    fence_regs(ca);
    fence_regs(oo);
    static_for<6>([&](auto PP) { store_out(PP, ca); });
    fence_async_proxy();
    __syncwarp();
    send_out(wprev, true);
  }
  if (k == nk + 1) mbar_wait(xbar_o, j ? par : par ^ 1);
  mbar_wait(sbase + B_DONE, 0);
  uint32_t failed = 0;
#pragma unroll
  for (int i = 0; i < 4; i++) {
    const uint4 f = lds128(sbase + OFF_FAIL + 512 * i + l16);
    failed |= f.x | f.y | f.z | f.w;
  }
  if (__any_sync(0xffffffffu, failed != 0)) {
    asm volatile("cp.async.bulk.wait_group 0;" ::: "memory");
    asm volatile("fence.proxy.async;" ::: "memory");
    for (int kk = 0; kk < nk; kk++) {
      uint32_t f = 0;
      for (int i = 0; i < 8; i++) f |= lds32(sbase + OFF_FAIL + 1024 * (i >> 2) + 512 * (kk & 1) + 128 * (i & 3) + 4 * (kk >> 6));
      if ((f >> ((kk >> 1) & 31)) & 1) redo_window(P, reinterpret_cast<float*>(smem_raw), window_any(kk), rank);
    }
  }
  asm volatile("cp.async.bulk.wait_group.read 0;" ::: "memory");
}

typedef CUresult (*EncodeTiledFn)(CUtensorMap*, CUtensorMapDataType, cuuint32_t, void*, const cuuint64_t*, const cuuint64_t*,
                                  const cuuint32_t*, const cuuint32_t*, CUtensorMapInterleave, CUtensorMapSwizzle,
                                  CUtensorMapL2promotion, CUtensorMapFloatOOBfill);

void encode_image_map(EncodeTiledFn fn, CUtensorMap* tm, void* ptr, uint32_t group_c, CUtensorMapSwizzle sw) {
  const cuuint64_t dims[5] = {(cuuint64_t)group_c, 2, (cuuint64_t)IMG, (cuuint64_t)IMG / 2, (cuuint64_t)(CH / group_c)};
  const cuuint64_t strides[4] = {(cuuint64_t)CH * 2, (cuuint64_t)CH * 2 * IMG, (cuuint64_t)CH * 4, (cuuint64_t)group_c * 2};
  const cuuint32_t box[5] = {group_c, 2, 4, 2, 3};
  const cuuint32_t estr[5] = {1, 1, 1, 1, 1};
  fn(tm, CU_TENSOR_MAP_DATA_TYPE_BFLOAT16, 5, ptr, dims, strides, box, estr, CU_TENSOR_MAP_INTERLEAVE_NONE, sw,
     CU_TENSOR_MAP_L2_PROMOTION_L2_128B, CU_TENSOR_MAP_FLOAT_OOB_FILL_NONE);
}
void encode_weight_map(EncodeTiledFn fn, CUtensorMap* tm, void* ptr, uint32_t cols) {
  const cuuint64_t dims[3] = {32, (cuuint64_t)CH, (cuuint64_t)(cols / 32)};
  const cuuint64_t strides[2] = {(cuuint64_t)cols * 2, 64};
  const cuuint32_t box[3] = {32, 96, 3};
  const cuuint32_t estr[3] = {1, 1, 1};
  fn(tm, CU_TENSOR_MAP_DATA_TYPE_BFLOAT16, 3, ptr, dims, strides, box, estr, CU_TENSOR_MAP_INTERLEAVE_NONE, CU_TENSOR_MAP_SWIZZLE_64B,
     CU_TENSOR_MAP_L2_PROMOTION_L2_128B, CU_TENSOR_MAP_FLOAT_OOB_FILL_NONE);
}

}

extern "C" void kernel_launch(void* const* d_in, const int* in_sizes, int n_in, void* d_out, int out_size) {
  (void)in_sizes; (void)n_in; (void)out_size;
  static int nclusters = 0;
  static EncodeTiledFn encode = nullptr;
  if (nclusters == 0) {
    cudaFuncSetAttribute(swin_attn_kernel, cudaFuncAttributeMaxDynamicSharedMemorySize, SMEM_BYTES);
    int dev = 0, sms = 0;
    cudaGetDevice(&dev);
    cudaDeviceGetAttribute(&sms, cudaDevAttrMultiProcessorCount, dev);
    nclusters = sms / 2;
    cudaLaunchConfig_t cfg = {};
    cfg.gridDim = dim3(2 * nclusters);
    cfg.blockDim = dim3(THREADS);
    cfg.dynamicSmemBytes = SMEM_BYTES;
    cudaLaunchAttribute at[1];
    at[0].id = cudaLaunchAttributeClusterDimension;
    at[0].val.clusterDim.x = 2; at[0].val.clusterDim.y = 1; at[0].val.clusterDim.z = 1;
    cfg.attrs = at; cfg.numAttrs = 1;
    int maxc = 0;
    if (cudaOccupancyMaxActiveClusters(&maxc, swin_attn_kernel, &cfg) == cudaSuccess && maxc > 0 && maxc < nclusters) nclusters = maxc;
    (void)cudaGetLastError();
    void* fn = nullptr;
    cudaDriverEntryPointQueryResult qres;
    cudaGetDriverEntryPoint("cuTensorMapEncodeTiled", &fn, cudaEnableDefault, &qres);
    encode = (EncodeTiledFn)fn;
  }
  CUtensorMap tm_x, tm_o, tm_w, tm_wo;
  encode_image_map(encode, &tm_x, d_in[0], 64, CU_TENSOR_MAP_SWIZZLE_128B);
  encode_image_map(encode, &tm_o, d_out, 32, CU_TENSOR_MAP_SWIZZLE_64B);
  encode_weight_map(encode, &tm_w, d_in[1], 3 * CH);
  encode_weight_map(encode, &tm_wo, d_in[2], CH);
  Params P;
  P.x = (const __nv_bfloat16*)d_in[0];
  P.wqkv = (const __nv_bfloat16*)d_in[1];
  P.wo = (const __nv_bfloat16*)d_in[2];
  P.rpb = (const __nv_bfloat16*)d_in[3];
  P.rp_idx = (const int*)d_in[4];
  P.mask = (const __nv_bfloat16*)d_in[5];
  P.out = (__nv_bfloat16*)d_out;
  P.wstride = nclusters;
  P.wskip = nclusters == 66 ? 16645 : 0;
  P.zero = 0;
  P.nk_min = NWIN / nclusters;
  P.nk_rem = NWIN % nclusters;
  swin_attn_kernel<<<2 * nclusters, THREADS, SMEM_BYTES, cudaStreamPerThread>>>(tm_x, tm_o, tm_w, tm_wo, P);
}
```

```cpp
#include <cuda_runtime.h>
#include <cuda_bf16.h>
#include <cuda.h>
#include <stdint.h>

namespace {

constexpr int IMG = 512, CH = 192, NWIN = 4096;
constexpr int THREADS = 256;

constexpr uint32_t OFF_X = 0;
constexpr uint32_t OFF_K = 24576;
constexpr uint32_t UB = 1536;
constexpr uint32_t OFF_V = OFF_K + 12288;
constexpr uint32_t OFF_L = OFF_V + 12288;
constexpr uint32_t OFF_W = OFF_L + 2 * 12288;
constexpr uint32_t W_HALF = 3 * 96 * 64, W_PART = 2 * W_HALF;
constexpr uint32_t WK = OFF_W, WQ = OFF_W + W_PART, WV = OFF_W + 2 * W_PART, WO = OFF_W + 3 * W_PART;
constexpr uint32_t OFF_BAR = OFF_W + 4 * W_PART;
constexpr uint32_t B_XFULL = 0;
constexpr uint32_t B_TOKEN = 32;
constexpr uint32_t B_KFREE = 40, B_VFREE = 48;
constexpr uint32_t B_EX0 = 56, B_EX1 = 64;
constexpr uint32_t B_LFREE = 72;
constexpr uint32_t B_X1 = 80;
constexpr uint32_t B_W = OFF_BAR + 256;
constexpr uint32_t B_IDX = OFF_BAR + 296;
constexpr uint32_t B_DONE = OFF_BAR + 304;
constexpr uint32_t OFF_DUMMY = OFF_BAR + 320;
constexpr uint32_t OFF_FAIL = OFF_BAR + 384;
constexpr uint32_t OFF_TAB = OFF_FAIL + 2048;
constexpr uint32_t OFF_END = OFF_TAB + 1024;
constexpr uint32_t SMEM_BYTES = OFF_END;

constexpr float LOG2E = 1.4426950408889634f;
constexpr float SCALE = 0.14433756729740643f;

__device__ __forceinline__ uint32_t smem_u32(const void* p) { return (uint32_t)__cvta_generic_to_shared(p); }
__device__ __forceinline__ void wg_fence() { asm volatile("wgmma.fence.sync.aligned;" ::: "memory"); }
__device__ __forceinline__ void wg_commit() { asm volatile("wgmma.commit_group.sync.aligned;" ::: "memory"); }
template <int N> __device__ __forceinline__ void wg_wait() { asm volatile("wgmma.wait_group.sync.aligned %0;" ::"n"(N) : "memory"); }
template <int N> __device__ __forceinline__ void fence_regs(float (&d)[N]) {
#pragma unroll
  for (int i = 0; i < N; i++) asm volatile("" : "+f"(d[i])::"memory");
}
template <int N> __device__ __forceinline__ void fence_regs(uint32_t (&d)[N]) {
#pragma unroll
  for (int i = 0; i < N; i++) asm volatile("" : "+r"(d[i])::"memory");
}
__device__ __forceinline__ bool elect_one() {
  uint32_t pred;
  asm volatile("{\n.reg .pred p;\nelect.sync _|p, 0xffffffff;\nselp.u32 %0, 1, 0, p;\n}\n" : "=r"(pred));
  return pred != 0;
}
__device__ __forceinline__ uint32_t pack_bf16(float lo, float hi) {
  uint32_t r;
  asm("cvt.rn.bf16x2.f32 %0, %1, %2;" : "=r"(r) : "f"(hi), "f"(lo));
  return r;
}
__device__ __forceinline__ float bf_lo(uint32_t v) { return __uint_as_float(v << 16); }
__device__ __forceinline__ float bf_hi(uint32_t v) { return __uint_as_float(v & 0xffff0000u); }
__device__ __forceinline__ float ex2(float x) {
  float y;
  asm("ex2.approx.ftz.f32 %0, %1;" : "=f"(y) : "f"(x));
  return y;
}
__device__ __forceinline__ uint32_t hadd2(uint32_t a, uint32_t b) {
  uint32_t r;
  asm("add.rn.bf16x2 %0, %1, %2;" : "=r"(r) : "r"(a), "r"(b));
  return r;
}
__device__ __forceinline__ uint32_t hmul2(uint32_t a, uint32_t b) {
  uint32_t r;
  asm("mul.rn.bf16x2 %0, %1, %2;" : "=r"(r) : "r"(a), "r"(b));
  return r;
}
__device__ __forceinline__ uint32_t dup_lo(uint32_t a) {
  uint32_t r;
  asm("{\n.reg .b16 l, h;\nmov.b32 {l, h}, %1;\nmov.b32 %0, {l, l};\n}\n" : "=r"(r) : "r"(a));
  return r;
}
__device__ __forceinline__ uint32_t dup_hi(uint32_t a) {
  uint32_t r;
  asm("{\n.reg .b16 l, h;\nmov.b32 {l, h}, %1;\nmov.b32 %0, {h, h};\n}\n" : "=r"(r) : "r"(a));
  return r;
}
__device__ __forceinline__ float rcp_approx(float x) {
  float y;
  asm("rcp.approx.ftz.f32 %0, %1;" : "=f"(y) : "f"(x));
  return y;
}
__device__ __forceinline__ uint4 ldg128(const void* p) {
  uint4 v;
  asm volatile("ld.global.L1::evict_normal.v4.u32 {%0,%1,%2,%3}, [%4];" : "=r"(v.x), "=r"(v.y), "=r"(v.z), "=r"(v.w) : "l"(p) : "memory");
  return v;
}
__device__ __forceinline__ void prefetch_l2(const void* p, uint32_t bytes) {
  asm volatile("cp.async.bulk.prefetch.L2.global [%0], %1;" ::"l"(p), "r"(bytes) : "memory");
}
__device__ __forceinline__ uint4 lds128(uint32_t addr) {
  uint4 v;
  asm volatile("ld.shared.v4.u32 {%0,%1,%2,%3}, [%4];" : "=r"(v.x), "=r"(v.y), "=r"(v.z), "=r"(v.w) : "r"(addr) : "memory");
  return v;
}
__device__ __forceinline__ uint4 lds128v(uint32_t addr) {
  uint4 v;
  asm volatile("ld.volatile.shared.v4.u32 {%0,%1,%2,%3}, [%4];" : "=r"(v.x), "=r"(v.y), "=r"(v.z), "=r"(v.w) : "r"(addr) : "memory");
  return v;
}
__device__ __forceinline__ uint32_t lds32(uint32_t addr) {
  uint32_t v;
  asm volatile("ld.shared.u32 %0, [%1];" : "=r"(v) : "r"(addr) : "memory");
  return v;
}
__device__ __forceinline__ void stmatrix_x4(uint32_t addr, uint32_t a, uint32_t b, uint32_t c, uint32_t d) {
  asm volatile("stmatrix.sync.aligned.m8n8.x4.shared.b16 [%0], {%1,%2,%3,%4};" ::"r"(addr), "r"(a), "r"(b), "r"(c), "r"(d) : "memory");
}
__device__ __forceinline__ void ldmatrix_x4(uint32_t addr, uint32_t& a, uint32_t& b, uint32_t& c, uint32_t& d) {
  asm volatile("ldmatrix.sync.aligned.m8n8.x4.shared.b16 {%0,%1,%2,%3}, [%4];" : "=r"(a), "=r"(b), "=r"(c), "=r"(d) : "r"(addr) : "memory");
}
__device__ __forceinline__ void fence_async_proxy() {
  asm volatile("fence.proxy.async.shared::cta;" ::: "memory");
}
__device__ __forceinline__ void wg_barrier(int j) { asm volatile("bar.sync %0, 128;" ::"r"(1 + j) : "memory"); }
__device__ __forceinline__ void cluster_wait() { asm volatile("barrier.cluster.wait.acquire.aligned;" ::: "memory"); }
__device__ __forceinline__ uint32_t mapa(uint32_t a, uint32_t rank) {
  uint32_t o;
  asm("mapa.shared::cluster.u32 %0, %1, %2;" : "=r"(o) : "r"(a), "r"(rank));
  return o;
}
__device__ __forceinline__ void mbar_init(uint32_t a, uint32_t cnt) { asm volatile("mbarrier.init.shared::cta.b64 [%0], %1;" ::"r"(a), "r"(cnt) : "memory"); }
__device__ __forceinline__ void mbar_expect_tx(uint32_t a, uint32_t tx) {
  asm volatile("mbarrier.arrive.expect_tx.shared::cta.b64 _, [%0], %1;" ::"r"(a), "r"(tx) : "memory");
}
__device__ __forceinline__ void mbar_arrive(uint32_t a) { asm volatile("mbarrier.arrive.shared::cta.b64 _, [%0];" ::"r"(a) : "memory"); }
__device__ __forceinline__ void mbar_arrive4(uint32_t a) { asm volatile("mbarrier.arrive.shared::cta.b64 _, [%0], 4;" ::"r"(a) : "memory"); }
__device__ __forceinline__ uint32_t uniform(uint32_t v) { return __shfl_sync(0xffffffffu, v, 0); }
__device__ __forceinline__ void mbar_arrive_remote_relaxed(uint32_t a) {
  asm volatile("mbarrier.arrive.relaxed.cluster.shared::cluster.b64 _, [%0];" ::"r"(a) : "memory");
}
__device__ __forceinline__ void mbar_wait(uint32_t a, uint32_t parity) {
  asm volatile(
      "{\n.reg .pred p;\n.reg .u32 n;\n"
      "mbarrier.try_wait.parity.shared::cta.b64 p, [%0], %1;\n"
      "@p bra WAIT_DONE;\n"
      "mov.u32 n, 0;\n"
      "WAIT_LOOP:\n"
      "add.u32 n, n, 1;\n"
      "setp.gt.u32 p, n, 4000000;\n"
      "@p trap;\n"
      "mbarrier.try_wait.parity.shared::cta.b64 p, [%0], %1;\n"
      "@!p bra WAIT_LOOP;\n"
      "WAIT_DONE:\n}\n" ::"r"(a), "r"(parity) : "memory");
}
__device__ __forceinline__ bool mbar_test(uint32_t a, uint32_t parity) {
  uint32_t ok;
  asm volatile("{\n.reg .pred p;\nmbarrier.test_wait.parity.shared::cta.b64 p, [%1], %2;\nselp.u32 %0, 1, 0, p;\n}\n" : "=r"(ok) : "r"(a), "r"(parity) : "memory");
  return ok != 0;
}
__device__ __forceinline__ uint32_t hfma2(uint32_t a, uint32_t b, uint32_t c) {
  uint32_t r;
  asm("fma.rn.bf16x2 %0, %1, %2, %3;" : "=r"(r) : "r"(a), "r"(b), "r"(c));
  return r;
}
__device__ __forceinline__ void st_async16(uint32_t raddr, uint32_t a, uint32_t b, uint32_t c, uint32_t d, uint32_t rbar) {
  asm volatile("st.async.weak.shared::cluster.mbarrier::complete_tx::bytes.v4.b32 [%0], {%1,%2,%3,%4}, [%5];" ::"r"(raddr),
               "r"(a), "r"(b), "r"(c), "r"(d), "r"(rbar) : "memory");
}

__device__ __forceinline__ void st_async4(uint32_t raddr, uint32_t v, uint32_t rbar) {
  asm volatile("st.async.weak.shared::cluster.mbarrier::complete_tx::bytes.b32 [%0], %1, [%2];" ::"r"(raddr), "r"(v), "r"(rbar) : "memory");
}
__device__ __forceinline__ void sts128(uint32_t addr, uint4 v) {
  asm volatile("st.shared.v4.u32 [%0], {%1,%2,%3,%4};" ::"r"(addr), "r"(v.x), "r"(v.y), "r"(v.z), "r"(v.w) : "memory");
}
__device__ __forceinline__ void bulk_load(uint32_t dst, const void* src, uint32_t bytes, uint32_t bar) {
  asm volatile("cp.async.bulk.shared::cta.global.mbarrier::complete_tx::bytes [%0], [%1], %2, [%3];" ::"r"(dst), "l"(src),
               "r"(bytes), "r"(bar) : "memory");
}
__device__ __forceinline__ void tma_load3(uint32_t dst, const CUtensorMap* tm, int c1, int c2, uint32_t bar) {
  asm volatile("cp.async.bulk.tensor.3d.shared::cta.global.tile.mbarrier::complete_tx::bytes [%0], [%1, {0, %2, %3}], [%4];" ::"r"(dst),
               "l"(tm), "r"(c1), "r"(c2), "r"(bar) : "memory");
}
__device__ __forceinline__ void tma_load5(uint32_t dst, const CUtensorMap* tm, int c2, int c3, uint32_t bar) {
  asm volatile("cp.async.bulk.tensor.5d.shared::cta.global.tile.mbarrier::complete_tx::bytes [%0], [%1, {0, 0, %2, %3, 0}], [%4];" ::"r"(dst),
               "l"(tm), "r"(c2), "r"(c3), "r"(bar) : "memory");
}
__device__ __forceinline__ void tma_store5(const CUtensorMap* tm, int c2, int c3, int c4, uint32_t src, uint64_t policy) {
  asm volatile("cp.async.bulk.tensor.5d.global.shared::cta.tile.bulk_group.L2::cache_hint [%0, {0, 0, %1, %2, %3}], [%4], %5;" ::"l"(tm),
               "r"(c2), "r"(c3), "r"(c4), "r"(src), "l"(policy) : "memory");
}
__device__ __forceinline__ void sched_barrier(uint32_t& t, uint32_t zero) {
  asm volatile("{\n.reg .pred p;\nsetp.ne.u32 p, %1, 0;\n@p mov.u32 %0, %%clock;\n}\n" : "+r"(t) : "r"(zero) : "memory");
}

__device__ __forceinline__ void wgmma_n48_a(float (&d)[24], uint32_t a0, uint32_t a1, uint32_t a2, uint32_t a3, uint64_t db) {
  asm volatile("{\n.reg .pred p;\nsetp.ne.b32 p, 1, 0;\n"
      "wgmma.mma_async.sync.aligned.m64n48k16.f32.bf16.bf16 "
      "{%0,%1,%2,%3,%4,%5,%6,%7,%8,%9,%10,%11,%12,%13,%14,%15,"
      "%16,%17,%18,%19,%20,%21,%22,%23}, "
      "{%24,%25,%26,%27}, %28, p, 1, 1, 1;\n}\n"
      : "+f"(d[0]), "+f"(d[1]), "+f"(d[2]), "+f"(d[3]), "+f"(d[4]), "+f"(d[5]), "+f"(d[6]), "+f"(d[7]),
        "+f"(d[8]), "+f"(d[9]), "+f"(d[10]), "+f"(d[11]), "+f"(d[12]), "+f"(d[13]), "+f"(d[14]), "+f"(d[15]),
        "+f"(d[16]), "+f"(d[17]), "+f"(d[18]), "+f"(d[19]), "+f"(d[20]), "+f"(d[21]), "+f"(d[22]), "+f"(d[23])
      : "r"(a0), "r"(a1), "r"(a2), "r"(a3), "l"(db));
}
__device__ __forceinline__ void wgmma_n48_z(float (&d)[24], uint32_t a0, uint32_t a1, uint32_t a2, uint32_t a3, uint64_t db) {
  asm volatile("{\n.reg .pred p;\nsetp.ne.b32 p, 0, 0;\n"
      "wgmma.mma_async.sync.aligned.m64n48k16.f32.bf16.bf16 "
      "{%0,%1,%2,%3,%4,%5,%6,%7,%8,%9,%10,%11,%12,%13,%14,%15,"
      "%16,%17,%18,%19,%20,%21,%22,%23}, "
      "{%24,%25,%26,%27}, %28, p, 1, 1, 1;\n}\n"
      : "=f"(d[0]), "=f"(d[1]), "=f"(d[2]), "=f"(d[3]), "=f"(d[4]), "=f"(d[5]), "=f"(d[6]), "=f"(d[7]),
        "=f"(d[8]), "=f"(d[9]), "=f"(d[10]), "=f"(d[11]), "=f"(d[12]), "=f"(d[13]), "=f"(d[14]), "=f"(d[15]),
        "=f"(d[16]), "=f"(d[17]), "=f"(d[18]), "=f"(d[19]), "=f"(d[20]), "=f"(d[21]), "=f"(d[22]), "=f"(d[23])
      : "r"(a0), "r"(a1), "r"(a2), "r"(a3), "l"(db));
}
__device__ __forceinline__ void wgmma_n96_a(float (&d)[48], uint32_t a0, uint32_t a1, uint32_t a2, uint32_t a3, uint64_t db) {
  asm volatile("{\n.reg .pred p;\nsetp.ne.b32 p, 1, 0;\n"
      "wgmma.mma_async.sync.aligned.m64n96k16.f32.bf16.bf16 "
      "{%0,%1,%2,%3,%4,%5,%6,%7,%8,%9,%10,%11,%12,%13,%14,%15,"
      "%16,%17,%18,%19,%20,%21,%22,%23,%24,%25,%26,%27,%28,%29,%30,%31,"
      "%32,%33,%34,%35,%36,%37,%38,%39,%40,%41,%42,%43,%44,%45,%46,%47}, "
      "{%48,%49,%50,%51}, %52, p, 1, 1, 1;\n}\n"
      : "+f"(d[0]), "+f"(d[1]), "+f"(d[2]), "+f"(d[3]), "+f"(d[4]), "+f"(d[5]), "+f"(d[6]), "+f"(d[7]),
        "+f"(d[8]), "+f"(d[9]), "+f"(d[10]), "+f"(d[11]), "+f"(d[12]), "+f"(d[13]), "+f"(d[14]), "+f"(d[15]),
        "+f"(d[16]), "+f"(d[17]), "+f"(d[18]), "+f"(d[19]), "+f"(d[20]), "+f"(d[21]), "+f"(d[22]), "+f"(d[23]),
        "+f"(d[24]), "+f"(d[25]), "+f"(d[26]), "+f"(d[27]), "+f"(d[28]), "+f"(d[29]), "+f"(d[30]), "+f"(d[31]),
        "+f"(d[32]), "+f"(d[33]), "+f"(d[34]), "+f"(d[35]), "+f"(d[36]), "+f"(d[37]), "+f"(d[38]), "+f"(d[39]),
        "+f"(d[40]), "+f"(d[41]), "+f"(d[42]), "+f"(d[43]), "+f"(d[44]), "+f"(d[45]), "+f"(d[46]), "+f"(d[47])
      : "r"(a0), "r"(a1), "r"(a2), "r"(a3), "l"(db));
}
__device__ __forceinline__ void wgmma_n96_z(float (&d)[48], uint32_t a0, uint32_t a1, uint32_t a2, uint32_t a3, uint64_t db) {
  asm volatile("{\n.reg .pred p;\nsetp.ne.b32 p, 0, 0;\n"
      "wgmma.mma_async.sync.aligned.m64n96k16.f32.bf16.bf16 "
      "{%0,%1,%2,%3,%4,%5,%6,%7,%8,%9,%10,%11,%12,%13,%14,%15,"
      "%16,%17,%18,%19,%20,%21,%22,%23,%24,%25,%26,%27,%28,%29,%30,%31,"
      "%32,%33,%34,%35,%36,%37,%38,%39,%40,%41,%42,%43,%44,%45,%46,%47}, "
      "{%48,%49,%50,%51}, %52, p, 1, 1, 1;\n}\n"
      : "=f"(d[0]), "=f"(d[1]), "=f"(d[2]), "=f"(d[3]), "=f"(d[4]), "=f"(d[5]), "=f"(d[6]), "=f"(d[7]),
        "=f"(d[8]), "=f"(d[9]), "=f"(d[10]), "=f"(d[11]), "=f"(d[12]), "=f"(d[13]), "=f"(d[14]), "=f"(d[15]),
        "=f"(d[16]), "=f"(d[17]), "=f"(d[18]), "=f"(d[19]), "=f"(d[20]), "=f"(d[21]), "=f"(d[22]), "=f"(d[23]),
        "=f"(d[24]), "=f"(d[25]), "=f"(d[26]), "=f"(d[27]), "=f"(d[28]), "=f"(d[29]), "=f"(d[30]), "=f"(d[31]),
        "=f"(d[32]), "=f"(d[33]), "=f"(d[34]), "=f"(d[35]), "=f"(d[36]), "=f"(d[37]), "=f"(d[38]), "=f"(d[39]),
        "=f"(d[40]), "=f"(d[41]), "=f"(d[42]), "=f"(d[43]), "=f"(d[44]), "=f"(d[45]), "=f"(d[46]), "=f"(d[47])
      : "r"(a0), "r"(a1), "r"(a2), "r"(a3), "l"(db));
}
__device__ __forceinline__ void wgmma_n96_p(float (&d)[48], uint32_t a0, uint32_t a1, uint32_t a2, uint32_t a3, uint64_t db, uint32_t acc) {
  asm volatile("{\n.reg .pred p;\nsetp.ne.b32 p, %53, 0;\n"
      "wgmma.mma_async.sync.aligned.m64n96k16.f32.bf16.bf16 "
      "{%0,%1,%2,%3,%4,%5,%6,%7,%8,%9,%10,%11,%12,%13,%14,%15,"
      "%16,%17,%18,%19,%20,%21,%22,%23,%24,%25,%26,%27,%28,%29,%30,%31,"
      "%32,%33,%34,%35,%36,%37,%38,%39,%40,%41,%42,%43,%44,%45,%46,%47}, "
      "{%48,%49,%50,%51}, %52, p, 1, 1, 1;\n}\n"
      : "+f"(d[0]), "+f"(d[1]), "+f"(d[2]), "+f"(d[3]), "+f"(d[4]), "+f"(d[5]), "+f"(d[6]), "+f"(d[7]),
        "+f"(d[8]), "+f"(d[9]), "+f"(d[10]), "+f"(d[11]), "+f"(d[12]), "+f"(d[13]), "+f"(d[14]), "+f"(d[15]),
        "+f"(d[16]), "+f"(d[17]), "+f"(d[18]), "+f"(d[19]), "+f"(d[20]), "+f"(d[21]), "+f"(d[22]), "+f"(d[23]),
        "+f"(d[24]), "+f"(d[25]), "+f"(d[26]), "+f"(d[27]), "+f"(d[28]), "+f"(d[29]), "+f"(d[30]), "+f"(d[31]),
        "+f"(d[32]), "+f"(d[33]), "+f"(d[34]), "+f"(d[35]), "+f"(d[36]), "+f"(d[37]), "+f"(d[38]), "+f"(d[39]),
        "+f"(d[40]), "+f"(d[41]), "+f"(d[42]), "+f"(d[43]), "+f"(d[44]), "+f"(d[45]), "+f"(d[46]), "+f"(d[47])
      : "r"(a0), "r"(a1), "r"(a2), "r"(a3), "l"(db), "r"(acc));
}
__device__ __forceinline__ void wgmma_n64_a(float (&d)[32], uint32_t a0, uint32_t a1, uint32_t a2, uint32_t a3, uint64_t db) {
  asm volatile("{\n.reg .pred p;\nsetp.ne.b32 p, 1, 0;\n"
      "wgmma.mma_async.sync.aligned.m64n64k16.f32.bf16.bf16 "
      "{%0,%1,%2,%3,%4,%5,%6,%7,%8,%9,%10,%11,%12,%13,%14,%15,"
      "%16,%17,%18,%19,%20,%21,%22,%23,%24,%25,%26,%27,%28,%29,%30,%31}, "
      "{%32,%33,%34,%35}, %36, p, 1, 1, 0;\n}\n"
      : "+f"(d[0]), "+f"(d[1]), "+f"(d[2]), "+f"(d[3]), "+f"(d[4]), "+f"(d[5]), "+f"(d[6]), "+f"(d[7]),
        "+f"(d[8]), "+f"(d[9]), "+f"(d[10]), "+f"(d[11]), "+f"(d[12]), "+f"(d[13]), "+f"(d[14]), "+f"(d[15]),
        "+f"(d[16]), "+f"(d[17]), "+f"(d[18]), "+f"(d[19]), "+f"(d[20]), "+f"(d[21]), "+f"(d[22]), "+f"(d[23]),
        "+f"(d[24]), "+f"(d[25]), "+f"(d[26]), "+f"(d[27]), "+f"(d[28]), "+f"(d[29]), "+f"(d[30]), "+f"(d[31])
      : "r"(a0), "r"(a1), "r"(a2), "r"(a3), "l"(db));
}
__device__ __forceinline__ void wgmma_n64_z(float (&d)[32], uint32_t a0, uint32_t a1, uint32_t a2, uint32_t a3, uint64_t db) {
  asm volatile("{\n.reg .pred p;\nsetp.ne.b32 p, 0, 0;\n"
      "wgmma.mma_async.sync.aligned.m64n64k16.f32.bf16.bf16 "
      "{%0,%1,%2,%3,%4,%5,%6,%7,%8,%9,%10,%11,%12,%13,%14,%15,"
      "%16,%17,%18,%19,%20,%21,%22,%23,%24,%25,%26,%27,%28,%29,%30,%31}, "
      "{%32,%33,%34,%35}, %36, p, 1, 1, 0;\n}\n"
      : "=f"(d[0]), "=f"(d[1]), "=f"(d[2]), "=f"(d[3]), "=f"(d[4]), "=f"(d[5]), "=f"(d[6]), "=f"(d[7]),
        "=f"(d[8]), "=f"(d[9]), "=f"(d[10]), "=f"(d[11]), "=f"(d[12]), "=f"(d[13]), "=f"(d[14]), "=f"(d[15]),
        "=f"(d[16]), "=f"(d[17]), "=f"(d[18]), "=f"(d[19]), "=f"(d[20]), "=f"(d[21]), "=f"(d[22]), "=f"(d[23]),
        "=f"(d[24]), "=f"(d[25]), "=f"(d[26]), "=f"(d[27]), "=f"(d[28]), "=f"(d[29]), "=f"(d[30]), "=f"(d[31])
      : "r"(a0), "r"(a1), "r"(a2), "r"(a3), "l"(db));
}

template <uint32_t OFF, uint32_t LBO>
__device__ __forceinline__ uint64_t desc_at(uint64_t base) {
  return base + (uint64_t)((OFF >> 4) + ((LBO >> 4) << 16));
}
template <uint32_t SBO, uint32_t SWIZZLE = 0>
__device__ __forceinline__ uint64_t desc_base(uint32_t addr4) {
  return ((uint64_t)SWIZZLE << 62) | ((uint64_t)(SBO >> 4) << 32) | (uint64_t)addr4;
}
__device__ __forceinline__ uint64_t pin(uint64_t v) {
  asm volatile("" : "+l"(v));
  return v;
}
template <int I> struct IC { static constexpr int v = I; };
template <int N, class F> __device__ __forceinline__ void static_for(F&& f) {
  if constexpr (N > 0) { static_for<N - 1>(f); f(IC<N - 1>{}); }
}

__device__ __forceinline__ void quad_origin(int win, int w, bool valid, int& row, int& col2) {
  col2 = (4 * (win & 63) + 2 + 2 * (w & 1)) & (IMG / 2 - 1);
  row = (8 * (win >> 6) + 4 + 4 * (w >> 1)) & (IMG - 1);
  if (!valid) row = IMG;
}
__device__ __forceinline__ void load_tile(uint32_t dst, int warp, int win, bool valid, uint32_t xbar, const CUtensorMap* tm_x) {
  int row, col2;
  quad_origin(win, warp, valid, row, col2);
  if (elect_one()) {
    mbar_expect_tx(xbar, 6144);
    tma_load5(dst, tm_x, row, col2, xbar);
  }
}
template <int S>
__device__ __forceinline__ void read_x(uint32_t (&xa)[48], const uint32_t (&xaddr)[4]) {
  ldmatrix_x4(xaddr[S & 3] + (S >> 2) * 2048, xa[4 * S], xa[4 * S + 1], xa[4 * S + 2], xa[4 * S + 3]);
}
__device__ __forceinline__ void reads_done(uint32_t last, uint32_t dummy_addr) {
  asm volatile("{\n.reg .pred p;\nsetp.eq.u32 p, %0, 0x7fc1fc17;\n@p st.shared.u32 [%1], %0;\n}\n" ::"r"(last), "r"(dummy_addr) : "memory");
}
template <int P>
__device__ __forceinline__ void store_chunk(uint32_t addr, float (&d)[48]) {
  stmatrix_x4(addr, pack_bf16(d[8 * P + 0], d[8 * P + 1]), pack_bf16(d[8 * P + 2], d[8 * P + 3]),
              pack_bf16(d[8 * P + 4], d[8 * P + 5]), pack_bf16(d[8 * P + 6], d[8 * P + 7]));
}
constexpr int IDLE = -100;
template <uint32_t WOFF, int H, bool TIED, class F>
__device__ __forceinline__ void gemm_phase(float (&run)[48], uint32_t (&x)[48], uint64_t w4, uint32_t rzero, F&& after) {
  wg_fence();
  static_for<12>([&](auto I) {
    constexpr int s = decltype(I)::v;
    const uint64_t d = desc_at<WOFF + (s / 6) * W_HALF + (s % 6) * 1024, 6144>(pin(w4));
    if constexpr (s == 0 && TIED) wgmma_n96_p(run, x[0], x[1], x[2], x[3], d, rzero);
    else if constexpr (s == 0) wgmma_n96_z(run, x[0], x[1], x[2], x[3], d);
    else wgmma_n96_a(run, x[4 * s], x[4 * s + 1], x[4 * s + 2], x[4 * s + 3], d);
    if constexpr (s == H - 1 || s == 11) wg_commit();
    if constexpr (s == H - 1) { after(IC<IDLE>{}); wg_wait<1>(); }
    after(I);
  });
}
template <int H>
__device__ __forceinline__ void issue_s(float (&s)[32], uint32_t (&q)[24], uint64_t k4_) {
  const uint64_t k4 = pin(k4_);
  static_for<3>([&](auto I) {
    constexpr int k = decltype(I)::v, i = 12 * H + 4 * k;
    const uint64_t d = desc_at<OFF_K + H * 768 + k * 256, 128>(k4);
    if constexpr (k == 0) wgmma_n64_z(s, q[i], q[i + 1], q[i + 2], q[i + 3], d);
    else wgmma_n64_a(s, q[i], q[i + 1], q[i + 2], q[i + 3], d);
  });
  wg_commit();
}
__device__ __forceinline__ const uint8_t* offset_ptr(const uint8_t* base, uint32_t off) {
  const uint8_t* r;
  asm volatile("{\n.reg .u64 o;\ncvt.u64.u32 o, %2;\nadd.u64 %0, %1, o;\n}\n" : "=l"(r) : "l"(base), "r"(off));
  return r;
}
struct MaskRows { uint4 a, b, c, d; };
__device__ __forceinline__ MaskRows mask_load(const uint8_t* mp) {
  MaskRows r;
  r.a = ldg128(mp); r.b = ldg128(mp + 1024); r.c = ldg128(mp + 2048); r.d = ldg128(mp + 3072);
  return r;
}
__device__ __forceinline__ void pin_rows(MaskRows& r) {
  asm volatile("" : "+r"(r.a.x), "+r"(r.a.y), "+r"(r.a.z), "+r"(r.a.w), "+r"(r.b.x), "+r"(r.b.y), "+r"(r.b.z), "+r"(r.b.w),
                    "+r"(r.c.x), "+r"(r.c.y), "+r"(r.c.z), "+r"(r.c.w), "+r"(r.d.x), "+r"(r.d.y), "+r"(r.d.z), "+r"(r.d.w)::"memory");
}
__device__ __forceinline__ uint32_t mask_or(const MaskRows& r) {
  return (r.a.x | r.a.y | r.a.z | r.a.w) | (r.b.x | r.b.y | r.b.z | r.b.w) | (r.c.x | r.c.y | r.c.z | r.c.w) | (r.d.x | r.d.y | r.d.z | r.d.w);
}
__device__ __forceinline__ void add_mask(float (&s0)[32], float (&s1)[32], const uint4 (&m)[4]) {
#pragma unroll
  for (int t = 0; t < 2; t++) {
#pragma unroll
    for (int b = 0; b < 8; b++) {
      const uint4 u = m[2 * t + (b >> 2)];
      const uint32_t v = (b & 3) == 0 ? u.x : (b & 3) == 1 ? u.y : (b & 3) == 2 ? u.z : u.w;
      const int i = 4 * b + 2 * t;
      s0[i] = fmaf(bf_lo(v), LOG2E, s0[i]); s0[i + 1] = fmaf(bf_hi(v), LOG2E, s0[i + 1]);
      s1[i] = fmaf(bf_lo(v), LOG2E, s1[i]); s1[i + 1] = fmaf(bf_hi(v), LOG2E, s1[i + 1]);
    }
  }
}
__device__ __forceinline__ void subtract_row_max(float (&s)[32]) {
#pragma unroll
  for (int t = 0; t < 2; t++) {
    float x = -INFINITY;
#pragma unroll
    for (int b = 0; b < 8; b++) x = fmaxf(x, fmaxf(s[4 * b + 2 * t], s[4 * b + 2 * t + 1]));
    x = fmaxf(x, __shfl_xor_sync(0xffffffffu, x, 1));
    x = fmaxf(x, __shfl_xor_sync(0xffffffffu, x, 2));
#pragma unroll
    for (int b = 0; b < 8; b++) { s[4 * b + 2 * t] -= x; s[4 * b + 2 * t + 1] -= x; }
  }
}
template <int I0, int I1>
__device__ __forceinline__ void exp_pairs(float (&s)[32]) {
#pragma unroll
  for (int i = 2 * I0; i < 2 * I1; i++) {
    asm volatile("" : "+f"(s[i])::"memory");
    s[i] = ex2(s[i]);
    asm volatile("" : "+f"(s[i])::"memory");
  }
}
template <int I0, int I1>
__device__ __forceinline__ void pack_pairs(float (&s)[32], const uint32_t (&eb)[16], uint32_t (&p)[16], uint32_t (&z)[6]) {
#pragma unroll
  for (int i = I0; i < I1; i++) {
    asm volatile("" : "+f"(s[2 * i]), "+f"(s[2 * i + 1])::"memory");
    p[i] = hmul2(pack_bf16(s[2 * i], s[2 * i + 1]), eb[i]);
    asm volatile("" : "+r"(p[i])::"memory");
    const int b = i >> 1, t = i & 1;
    if (b & 1) {
      uint32_t v = hadd2(p[i - 2], p[i]);
      if (b & 2) v = hadd2(z[4 + t], v);
      if (b == 7) v = hadd2(z[2 + t], v);
      uint32_t& dst = z[(b == 7 ? 0 : (b & 2) ? 2 : 4) + t];
      dst = v;
      asm volatile("" : "+r"(dst)::"memory");
    }
  }
}
struct RowSums {
  uint32_t a, b, c, d;
  __device__ __forceinline__ void start(const uint32_t (&z)[6]) {
    a = hadd2(__byte_perm(z[0], z[1], 0x5410), __byte_perm(z[0], z[1], 0x7632));
    b = __shfl_xor_sync(0xffffffffu, a, 1);
    c = __shfl_xor_sync(0xffffffffu, a, 2);
    d = __shfl_xor_sync(0xffffffffu, a, 3);
  }
  __device__ __forceinline__ uint32_t finish() {
    asm volatile("" : "+r"(a), "+r"(b), "+r"(c), "+r"(d)::"memory");
    const uint32_t x = hadd2(a, b), y = hadd2(c, d);
    return pack_bf16(rcp_approx(bf_lo(x) + bf_lo(y)), rcp_approx(bf_hi(x) + bf_hi(y)));
  }
};
template <int H>
__device__ __forceinline__ void issue_pv(float (&oacc)[24], uint32_t (&p)[16], uint64_t v4_) {
  const uint64_t v4 = pin(v4_);
  static_for<4>([&](auto I) {
    constexpr int k = decltype(I)::v;
    const uint64_t d = desc_at<OFF_V + H * 6144 + k * 256, 128>(v4);
    if constexpr (k == 0) wgmma_n48_z(oacc, p[0], p[1], p[2], p[3], d);
    else wgmma_n48_a(oacc, p[4 * k], p[4 * k + 1], p[4 * k + 2], p[4 * k + 3], d);
  });
  wg_commit();
}
constexpr uint32_t BAD_SUM = 0xE000E000u;
template <int H>
__device__ __forceinline__ uint32_t normalize(float (&oacc)[24], uint32_t r, uint32_t (&o)[48]) {
  const uint32_t ra = dup_lo(r), rb = dup_hi(r);
#pragma unroll
  for (int k = 0; k < 12; k++) o[12 * H + k] = hmul2(pack_bf16(oacc[2 * k], oacc[2 * k + 1]), (k & 1) ? rb : ra);
  return r - 0x2F802F80u;
}

struct Params {
  const __nv_bfloat16 *x, *wqkv, *wo, *rpb;
  const int* rp_idx;
  const __nv_bfloat16* mask;
  __nv_bfloat16* out;
  int nk_min, nk_rem, wstride, wskip, zero;
};
__device__ __forceinline__ float round_bf16(float v) { return __bfloat162float(__float2bfloat16(v)); }
__device__ __forceinline__ void redo_window(const Params& P, float* sm, int win, int rank) {
  float* xt = sm;
  float* qkv = sm + 192 * 64;
  const int tid = threadIdx.x;
  auto pixel = [&](int n) { return (size_t)(((8 * (win >> 6) + (n >> 3) + 4) & (IMG - 1)) * IMG + ((8 * (win & 63) + (n & 7) + 4) & (IMG - 1))) * CH; };
  auto gemm = [&](const __nv_bfloat16* w, int ldw, int ncols, auto&& put) {
    for (int e = tid; e < 4 * ncols; e += THREADS) {
      const int g = e / ncols, d = e - g * ncols;
      float acc[16];
#pragma unroll
      for (int i = 0; i < 16; i++) acc[i] = 0.f;
      for (int c = 0; c < CH; c++) {
        const float wv = __bfloat162float(w[c * ldw + d]);
#pragma unroll
        for (int i = 0; i < 16; i++) acc[i] = fmaf(xt[c * 64 + 16 * g + i], wv, acc[i]);
      }
#pragma unroll
      for (int i = 0; i < 16; i++) put(16 * g + i, d, acc[i]);
    }
  };
  __syncthreads();
  for (int e = tid; e < 64 * CH; e += THREADS) xt[(e % CH) * 64 + e / CH] = __bfloat162float(P.x[pixel(e / CH) + e % CH]);
  __syncthreads();
  gemm(P.wqkv, 3 * CH, 3 * CH, [&](int n, int d, float v) { qkv[n * 577 + d] = round_bf16(v); });
  __syncthreads();
  {
    const int n = tid & 63, h = tid >> 6;
    auto logit = [&](int m) {
      float s = 0.f;
      for (int d = 0; d < 48; d++) s = fmaf(qkv[n * 577 + 48 * h + d], qkv[m * 577 + CH + 48 * h + d], s);
      return s * SCALE + __bfloat162float(P.rpb[P.rp_idx[n * 64 + m] * 4 + h]) + __bfloat162float(P.mask[(size_t)win * 4096 + n * 64 + m]);
    };
    float mx = -INFINITY, sum = 0.f, o[48];
    for (int m = 0; m < 64; m++) mx = fmaxf(mx, logit(m));
#pragma unroll
    for (int d = 0; d < 48; d++) o[d] = 0.f;
    for (int m = 0; m < 64; m++) {
      const float p = expf(logit(m) - mx);
      sum += p;
#pragma unroll
      for (int d = 0; d < 48; d++) o[d] = fmaf(p, qkv[m * 577 + 2 * CH + 48 * h + d], o[d]);
    }
#pragma unroll
    for (int d = 0; d < 48; d++) xt[(48 * h + d) * 64 + n] = round_bf16(o[d] / sum);
  }
  __syncthreads();
  gemm(P.wo + 96 * rank, CH, 96, [&](int n, int d, float v) { P.out[pixel(n) + 96 * rank + d] = __float2bfloat16(v); });
}

#define HO 6
#define HQ 6
#define HV 6
#define E0 5
#define E1 15
#define ET 3
#define XSL "11110022220000"
#define XD 11
#define MS 8
#define KF 2
#define LF 9
#define NB 4
#define LAG 3
#define RA 0
#define QP 0
#define X1P 1
#define VP 2
#define X2P 4
#define K1W 1
#define HF 6
#define OF 5
#define AP 10
__host__ __device__ constexpr int g0(int r) { return r < 5 ? 3 * r : 16; }
__host__ __device__ constexpr int g1(int r) { return NB + (16 - NB) * r / 4; }
__host__ __device__ constexpr int xslot(int i) { return XSL[i] - '0'; }
__host__ __device__ constexpr int xbase(int i) { int b = 0; for (int q = 0; q < i; q++) b += xslot(q); return b; }
__host__ __device__ constexpr int xlast() { int l = 0; for (int q = 0; q < 14; q++) if (xslot(q)) l = q; return l; }
static_assert(xbase(14) == 12 && XD >= xlast(), "X schedule");

__global__ void __cluster_dims__(2, 1, 1) __launch_bounds__(THREADS, 1)
swin_attn_kernel(const __grid_constant__ CUtensorMap tm_x, const __grid_constant__ CUtensorMap tm_o, const __grid_constant__ CUtensorMap tm_w,
                 const __grid_constant__ CUtensorMap tm_wo, const __grid_constant__ Params P) {
  extern __shared__ __align__(1024) uint8_t smem_raw[];
  const uint32_t sbase = smem_u32(smem_raw);
  const int tid = threadIdx.x;
  const int wid = uniform(tid >> 5);
  const int j = wid >> 2, warp = wid & 3;
  const uint32_t lane = tid & 31;
  uint32_t rank;
  asm("mov.u32 %0, %%cluster_ctarank;" : "=r"(rank));
  auto load_w = [&](int part) {
#pragma unroll
    for (int h = 0; h < 2; h++) {
      const uint32_t b = sbase + B_W + (part == 0 && h == 0 ? 32 : 8 * part);
      if (part == 0 || h == 0) mbar_expect_tx(b, part == 0 ? W_HALF : W_PART);
      if (part < 3) tma_load3(sbase + OFF_W + part * W_PART + h * W_HALF, &tm_w, 96 * h, (part == 0 ? 6 : part == 1 ? 0 : 12) + 3 * rank, b);
      else tma_load3(sbase + WO + h * W_HALF, &tm_wo, 96 * (rank ^ h), 3 * rank, b);
    }
  };
  uint32_t tab[4] = {0, 0, 0, 0};
  if ((wid >> 1) == 2) {
    const uint32_t* tp = reinterpret_cast<const uint32_t*>(P.rpb) + 2 * (tid - 128) + rank;
#pragma unroll
    for (int i = 0; i < 4; i++)
      if (i < 3 || tid < 128 + 33) asm volatile("ld.global.nc.u32 %0, [%1];" : "=r"(tab[i]) : "l"(tp + 128 * i) : "memory");
    if (elect_one()) {
      const uint32_t b = sbase + OFF_BAR + 128 * (wid & 1);
#pragma unroll
      for (uint32_t o = B_TOKEN; o <= B_LFREE; o += 8) mbar_init(b + o, 4);
      if (wid == 4) {
        mbar_arrive4(b + B_TOKEN);
        mbar_arrive4(b + B_KFREE);
        mbar_arrive4(b + B_VFREE);
      } else {
        mbar_init(sbase + B_DONE, 8);
      }
      asm volatile("fence.mbarrier_init.release.cluster;" ::: "memory");
    }
  } else {
    if (wid == 7 && lane < 18 && blockIdx.x < 128)
      asm volatile("prefetch.global.L2 [%0];" ::"l"((blockIdx.x < 96 ? reinterpret_cast<const uint8_t*>(P.wqkv) + blockIdx.x * 2304 : reinterpret_cast<const uint8_t*>(P.wo) + (blockIdx.x - 96) * 2304) + lane * 128) : "memory");
    if (elect_one()) {
      const uint32_t b0 = sbase + (j == 0 ? OFF_BAR + B_XFULL + 8 * warp : wid == 6 ? B_IDX : B_W);
      const uint32_t b1 = sbase + (j == 0 ? OFF_BAR + 128 + B_XFULL + 8 * warp : wid == 6 ? B_W + 8 : B_W + 32);
      const uint32_t b2 = sbase + (j == 0 ? OFF_BAR + 128 + B_X1 + 8 * warp : wid == 6 ? B_W + 16 : B_W + 24);
      mbar_init(b0, 1);
      mbar_init(b1, 1);
      mbar_init(b2, 1);
      if (j == 0) mbar_arrive(b1);
      fence_async_proxy();
      if (wid == 6) {
        mbar_expect_tx(sbase + B_IDX, 16384);
        bulk_load(sbase + WO, P.rp_idx, 16384, sbase + B_IDX);
      }
    }
  }
  __syncwarp();
  int cluster = blockIdx.x >> 1;
  if (AP && P.wskip != 0) cluster = cluster < 4 ? AP + 8 * cluster : ((cluster - AP) & ~24) == 0 ? (cluster - AP) >> 3 : cluster;
  const int nk = uniform(P.nk_min + (cluster < P.nk_rem) + (tid >> 10));
  const bool special = P.wskip != 0;
  const int nspecial = (!special || cluster < 4) ? 0 : cluster < 7 ? 3 : 2;
  const int wbase = special ? cluster - 127 : cluster;
  auto inner = [&](int a) { return a + (int)((uint32_t)(a * P.wskip) >> 20); };
  auto window = [&](int k) { return inner(wbase + k * P.wstride); };
  auto window_any = [&](int k) {
    const int v = k == 2 ? cluster - 4 : k == 3 ? cluster + 61 : 58 + cluster, b = v < 64 ? 64 * v + 63 : 3968 + v;
    const int u = k == 0 ? cluster : k == 1 ? (cluster < 4 ? 66 : 63) + cluster : 121 + 4 * k + cluster;
    return (k >= 4 || !special) ? window(k) : k < 4 - nspecial ? inner(u) : b;
  };
  int win = window_any(j);
  const uint8_t* mask_b = reinterpret_cast<const uint8_t*>(P.mask);
  const uint32_t quad_row = 32 * (warp >> 1) + 4 * (warp & 1);
  const uint8_t* mask_q0 = mask_b + quad_row * 128;
  MaskRows mr;
  if (j == 0) {
    mr = mask_load(mask_q0 + (size_t)win * 8192 + lane * 16);
    load_tile(sbase + OFF_X + warp * 6144, warp, win, true, sbase + OFF_BAR + B_XFULL + 8 * warp, &tm_x);
  }
  if (wid == 7 && elect_one()) load_w(0);
  if (sbase & 1023) __trap();
  const uint32_t bar = uniform(smem_u32(smem_raw) + OFF_BAR + (tid & 128)), bar_o = uniform(smem_u32(smem_raw) + OFF_BAR + ((tid & 128) ^ 128));
  const uint32_t xbar = uniform(smem_u32(smem_raw) + OFF_BAR + (tid & 128) + B_XFULL + 8 * ((tid >> 5) & 3));
  const uint32_t xbar_o = uniform(smem_u32(smem_raw) + OFF_BAR + ((tid & 128) ^ 128) + B_XFULL + 8 * ((tid >> 5) & 3));
  const uint32_t xdst = uniform(smem_u32(smem_raw) + OFF_X + ((tid >> 5) & 3) * 6144);
  const uint32_t x1off = j == 0 ? 0 : warp < 2 ? OFF_L + 12288 : WO + 16384 - 12288;
  auto loads = [&](int step) {
    if (j == 1) {
      if (QP == step && warp == 0 && elect_one()) load_w(1);
      if (X1P == step) load_tile(xdst + x1off, warp, win, true, xbar + B_X1, &tm_x);
      if (VP == step && warp == 2 && elect_one()) load_w(2);
      if (X2P == step) load_tile(xdst, warp, window_any(2), 2 < nk, xbar_o, &tm_x);
    }
  };
  asm volatile("st.shared.u32 [%0], %1;" ::"r"(sbase + OFF_FAIL + 4 * tid), "r"(0) : "memory");
  bool big = false;
  if ((wid >> 1) == 2) {
#pragma unroll
    for (int i = 0; i < 4; i++) {
      const float b0 = bf_lo(tab[i]) * LOG2E, b1 = bf_hi(tab[i]) * LOG2E;
      asm volatile("st.shared.u32 [%0], %1;" ::"r"(sbase + OFF_TAB + 4 * (tid - 128) + 256 * i), "r"(pack_bf16(ex2(b0), ex2(b1))) : "memory");
      big = big || !(fabsf(b0) <= 60.f && fabsf(b1) <= 60.f);
    }
  }
  uint32_t force = __syncthreads_or(big) ? BAD_SUM : 0u;
  asm volatile("barrier.cluster.arrive.relaxed.aligned;" ::: "memory");
  loads(0);
  const uint32_t sb_a = uniform((sbase & 0x3FFFF) >> 4);
  const uint64_t w4 = desc_base<512, 2>(sb_a), k4 = desc_base<UB>(sb_a), v4 = desc_base<1024>(sb_a);
  const uint32_t blk = 2 * warp + ((lane >> 3) & 1);
  uint32_t stk = sbase + OFF_K + blk * UB + (lane >> 4) * 128 + (lane & 7) * 16;
  uint32_t stv = sbase + OFF_V + (lane >> 4) * 1024 + blk * 128 + (lane & 7) * 16;
  uint32_t xaddr0 = xdst + (lane & 15) * 128 + (((lane >> 4) ^ (lane & 7)) << 4);
  const uint32_t peer = rank ^ 1;
  const uint32_t area = uniform(smem_u32(smem_raw) + OFF_L + (tid >> 5) * 3072);
  const uint32_t r_bar = uniform(mapa(bar, peer)), r_area = uniform(mapa(area, peer));
  uint32_t l16 = lane * 16;
  uint32_t out_res = area + (lane & 15) * 64 + (((lane >> 4) ^ ((lane >> 1) & 3)) << 4);
  const uint32_t rzero = uniform(P.zero + (tid >> 10));
  const uint64_t mq = reinterpret_cast<uint64_t>(mask_b) + (32 * ((tid >> 6) & 1) + 4 * ((tid >> 5) & 1)) * 128;
  const uint8_t* mask_q = reinterpret_cast<const uint8_t*>(((uint64_t)uniform((uint32_t)(mq >> 32)) << 32) | uniform((uint32_t)mq));

  sched_barrier(stk, rzero); sched_barrier(stv, rzero); sched_barrier(xaddr0, rzero); sched_barrier(out_res, rzero); sched_barrier(l16, rzero);
  uint32_t ra[6], rb[6];
#pragma unroll
  for (int q = 0; q < 6; q++) {
    ra[q] = r_area + l16 + q * 512;
    rb[q] = r_bar + (q < 3 ? B_EX0 : B_EX1) + (tid >> 10);
    sched_barrier(ra[q], rzero);
    sched_barrier(rb[q], rzero);
  }
  uint32_t xa[48], oo[48], eb0[16], eb1[16];
  auto fetch = [&](auto H) {
    constexpr int o = 24 + 12 * decltype(H)::v;
    const uint32_t addr = area + l16 + 1536 * decltype(H)::v;
    const uint4 x = lds128v(addr), y = lds128v(addr + 512), z = lds128v(addr + 1024);
    oo[o + 0] = x.x; oo[o + 1] = x.y; oo[o + 2] = x.z; oo[o + 3] = x.w; oo[o + 4] = y.x; oo[o + 5] = y.y; oo[o + 6] = y.z; oo[o + 7] = y.w;
    oo[o + 8] = z.x; oo[o + 9] = z.y; oo[o + 10] = z.z; oo[o + 11] = z.w;
  };
  auto store_out = [&](auto PP, float (&d)[48]) {
    constexpr int p = decltype(PP)::v;
    store_chunk<p>(((p & 1) ? (out_res ^ 32) : out_res) + (p >> 1) * 1024, d);
  };
  uint64_t streaming;
  asm("createpolicy.fractional.L2::evict_first.b64 %0, 1.0;" : "=l"(streaming));
  auto send_out = [&](int w, bool valid) {
    int row, col2;
    quad_origin(w, warp, valid, row, col2);
    if (elect_one()) tma_store5(&tm_o, row, col2, 3 * rank, area, streaming);
    asm volatile("cp.async.bulk.commit_group;" ::: "memory");
  };
  auto prefetch_mask = [&](int w) {
    if (elect_one()) prefetch_l2(mask_b + (size_t)w * 8192 + (rank * 4 + warp) * 1024, 1024);
  };
  auto prefetch_x = [&](int w) {
    const int row = (8 * (w >> 6) + 4 + 4 * rank + warp) & (IMG - 1), col = 8 * (w & 63) + 4;
    if (elect_one()) prefetch_l2(reinterpret_cast<const uint8_t*>(P.x) + (size_t)(row * IMG + col) * (CH * 2), (w & 63) == 63 ? 4 * CH * 2 : 8 * CH * 2);
  };

  auto first_x = [&]() {
    uint32_t xaddr[4], all = ~0u;
#pragma unroll
    for (int q = 0; q < 4; q++) xaddr[q] = (xaddr0 + x1off) ^ (q << 5);
    mbar_wait(xbar + j * B_X1, 0);
    static_for<12>([&](auto I) { read_x<decltype(I)::v>(xa, xaddr); all &= xa[4 * decltype(I)::v + 3]; });
    reads_done(all, sbase + OFF_DUMMY);
  };
  auto gather = [&]() {
    const uint32_t odd = (l16 >> 6) & 1;
    const uint32_t ia = sbase + WO + (quad_row + 8 * (l16 >> 7) + odd) * 256 + (l16 & 0x30) * 2;
    mbar_wait(sbase + B_IDX, 0);
#pragma unroll
    for (int i = 0; i < 4; i++) {
      const int t = i >> 1, b = 4 * (i & 1);
      const uint4 u0 = lds128(ia + t * 512 + (i & 1) * 128 + odd * 16), u1 = lds128(ia + t * 512 + (i & 1) * 128 + 16 - odd * 16);
      const uint32_t id[8] = {u0.x, u0.y, u0.z, u0.w, u1.x, u1.y, u1.z, u1.w};
      uint32_t v[8];
#pragma unroll
      for (int q = 0; q < 8; q++) v[q] = lds32(sbase + OFF_TAB + 4 * id[q]);
#pragma unroll
      for (int q = 0; q < 4; q++) {
        const uint32_t x = odd ? v[(2 * q) ^ 4] : v[2 * q], y = odd ? v[(2 * q + 1) ^ 4] : v[2 * q + 1];
        eb0[2 * (b + q) + t] = __byte_perm(x, y, 0x5410);
        eb1[2 * (b + q) + t] = __byte_perm(x, y, 0x7632);
      }
    }
  };
  gather();
#pragma unroll
  for (int i = 0; i < 16; i += 4) {
    asm volatile("{\n.reg .pred p;\nsetp.ne.u32 p, %4, 0;\n@p ld.shared.v4.u32 {%0,%1,%2,%3}, [%4];\n}\n" : "+r"(eb0[i]), "+r"(eb0[i + 1]), "+r"(eb0[i + 2]), "+r"(eb0[i + 3]) : "r"(rzero));
    asm volatile("{\n.reg .pred p;\nsetp.ne.u32 p, %4, 0;\n@p ld.shared.v4.u32 {%0,%1,%2,%3}, [%4];\n}\n" : "+r"(eb1[i]), "+r"(eb1[i + 1]), "+r"(eb1[i + 2]), "+r"(eb1[i + 3]) : "r"(rzero));
  }
  loads(1);
#pragma unroll
  for (int h = 0; h < 2; h++) {
    constexpr uint32_t HI = 0x3E553E55u, LO = 0x396E396Eu;
    const uint32_t a = sbase + WK + h * 16384 + tid * 16;
    uint4 v[5];
    if (h == 0) mbar_wait(sbase + B_W + 32, 0);
    else mbar_wait(sbase + B_W, 0);
#pragma unroll
    for (int i = 0; i < 4 + h; i++) v[i] = lds128(a + i * 4096);
    loads(2 + h);
#pragma unroll
    for (int i = 0; i < 4 + h; i++)
      sts128(a + i * 4096, make_uint4(hfma2(v[i].x, HI, hmul2(v[i].x, LO)), hfma2(v[i].y, HI, hmul2(v[i].y, LO)),
                                      hfma2(v[i].z, HI, hmul2(v[i].z, LO)), hfma2(v[i].w, HI, hmul2(v[i].w, LO))));
  }
  fence_async_proxy();
  if (j == 0) first_x();
  bool masked = false;
  if (j == 0) {
    pin_rows(mr);
    masked = __any_sync(0xffffffffu, mask_or(mr) != 0);
  }
  __syncthreads();
  if (j == 1) {
    loads(4);
    mr = mask_load(mask_q0 + (size_t)win * 8192 + lane * 16);
    first_x();
    loads(5);
    wg_barrier(1);
    if (warp == 3 && elect_one()) load_w(3);
    if (2 < nk) prefetch_mask(window_any(2));
    if (3 < nk) {
      prefetch_x(window_any(3));
      prefetch_mask(window_any(3));
    }
    pin_rows(mr);
    masked = __any_sync(0xffffffffu, mask_or(mr) != 0);
  }

  uint32_t par = 0;
  auto sched = [&]() { sched_barrier(force, rzero); };
  int k = j, wprev = win, wnext = window_any(j + 2), wx = window_any(j + 3);
#pragma unroll
  for (int i = 0; i < 24; i++) oo[i] = 0;
  for (;;) {
    float ca[48], cb[48], s0[32], s1[32];
    uint32_t qf[24];
    const int wnn = window(k + 4);
    bool ex0, ex1, kfree;
    fence_regs(xa);
    if (k == j) {
      if (K1W == 1 && j == 1) mbar_wait(bar + B_TOKEN, 0);
      gemm_phase<WK, 0, false>(ca, xa, w4, rzero, [&](auto) {});
      cluster_wait();
      if (K1W == 2 && j == 1) mbar_wait(bar + B_TOKEN, 0);
      mbar_wait(sbase + B_W + 8, 0);
      gemm_phase<WQ, HF, false>(cb, xa, w4, rzero, [&](auto I) {
        constexpr int s = decltype(I)::v, p = s - (HF - 1);
        if constexpr (p == 0) { fence_regs(ca); mbar_wait(bar + B_KFREE, 0); }
        if constexpr (p >= 0 && p < 6) store_chunk<(p >= 0 && p < 6) ? p : 0>(stk + p * 256, ca);
      });
      mbar_wait(sbase + B_W + 16, 0);
      if (j == 1) mbar_wait(sbase + B_W + 24, 0);
    } else {
      auto exchange = [&](auto G) {
        constexpr int g = decltype(G)::v;
        if constexpr (g == E0 - ET) ex0 = mbar_test(bar + B_EX0, par ^ 1);
        if constexpr (g == E1 - ET) ex1 = mbar_test(bar + B_EX1, par ^ 1);
        if constexpr (g == E0) { if (!ex0) mbar_wait(bar + B_EX0, par ^ 1); fetch(IC<0>{}); }
        if constexpr (g == E1) { if (!ex1) mbar_wait(bar + B_EX1, par ^ 1); fetch(IC<1>{}); }
      };
      gemm_phase<WK, 0, false>(cb, xa, w4, rzero, [&](auto I) { exchange(I); });
      gemm_phase<WO, HO, false>(ca, oo, w4, rzero, [&](auto I) {
        constexpr int s = decltype(I)::v, p = s - (HO - 1);
        if constexpr (p == -2) kfree = mbar_test(bar + B_KFREE, par);
        if constexpr (p == 0) { fence_regs(cb); if (!kfree) mbar_wait(bar + B_KFREE, par); }
        if constexpr (p >= 0 && p < 6) store_chunk<(p >= 0 && p < 6) ? p : 0>(stk + p * 256, cb);
        exchange(IC<12 + s>{});
        if constexpr (s == OF) wg_fence();
      });
      gemm_phase<WQ, HQ, false>(cb, xa, w4, rzero, [&](auto I) {
        constexpr int s = decltype(I)::v, p = s - (HQ - 1);
        if constexpr (p == 0) { fence_regs(ca); }
        if constexpr (p >= 0 && p < 6) store_out(IC<(p >= 0 && p < 6) ? p : 0>{}, ca);
      });
    }
    gemm_phase<WV, HV, true>(ca, xa, w4, rzero, [&](auto I) {
      constexpr int s = decltype(I)::v, p = s - (HV - 1);
      if constexpr (s == IDLE) {
        if (k + 4 < nk) {
          prefetch_mask(wnn);
          prefetch_x(wnn);
        }
        if (l16 == 0) {
          mbar_expect_tx(bar + B_EX0, 1536);
          mbar_expect_tx(bar + B_EX1, 1536);
        }
      }
      if constexpr (p == 0) { fence_regs(cb); }
      if constexpr (p == 0) {
#pragma unroll
        for (int i = 0; i < 24; i++) qf[i] = pack_bf16(cb[2 * i], cb[2 * i + 1]);
      }
    });
    fence_regs(qf);
    fence_async_proxy();
    wg_barrier(j);
    wg_fence();
    issue_s<0>(s0, qf, k4);
    const bool vfree = mbar_test(bar + B_VFREE, par), xfull = mbar_test(xbar, par ^ 1);
    issue_s<1>(s1, qf, k4);
    if (l16 == 0) mbar_arrive(bar_o + B_TOKEN);
    send_out(wprev, k != j);
    uint32_t xaddr[4];
#pragma unroll
    for (int q = 0; q < 4; q++) xaddr[q] = xaddr0 ^ (q << 5);
    auto side = [&](auto R) {
      constexpr int r = decltype(R)::v, c = xslot(r), b = xbase(r);
      if constexpr (r == KF) {
        wg_wait<0>();
        fence_regs(s1);
        fence_regs(qf);
        if (l16 == 0) mbar_arrive(bar_o + B_KFREE);
      }
      if constexpr (r == LF) {
        asm volatile("cp.async.bulk.wait_group.read 0;" ::: "memory");
        __syncwarp();
        if (l16 == 0) mbar_arrive_remote_relaxed(r_bar + B_LFREE);
      }
      if constexpr (b == 0 && c > 0) { if (!xfull) mbar_wait(xbar, par ^ 1); }
      if constexpr (r == MS) mr = mask_load(offset_ptr(mask_q + (size_t)(k + 2 < nk ? wnext : win) * 8192, l16));
      static_for<c>([&](auto J) { read_x<b + decltype(J)::v>(xa, xaddr); });
      if constexpr (r == XD) {
        uint32_t all = ~0u;
#pragma unroll
        for (int i = 12 - xslot(xlast()); i < 12; i++) all &= xa[4 * i + 3];
        reads_done(all, sbase + OFF_DUMMY);
        load_tile(xdst, warp, wx, k + 3 < nk, xbar_o, &tm_x);
      }
    };
    auto store_v = [&](auto PP) { store_chunk<decltype(PP)::v>(stv + decltype(PP)::v * 2048, ca); };
    float o0[24], o1[24];
    uint32_t p0[16], p1[16], z0[6], z1[6], r0, r1;
    RowSums l0, l1;
    if (!vfree) mbar_wait(bar + B_VFREE, par);
    wg_wait<2>();
    fence_regs(ca);
    fence_regs(xa);
    store_v(IC<0>{});
    side(IC<0>{});
    store_v(IC<1>{});
    wg_wait<1>();
    fence_regs(s0);
    static_for<5>([&](auto R) {
      constexpr int r = decltype(R)::v;
      side(IC<1 + r>{});
      if constexpr (r == 0) {
        if (masked) {
          uint32_t l = l16;
          asm volatile("" : "+r"(l));
          const uint8_t* mp = offset_ptr(mask_q + (size_t)win * 8192, (l & 0x180) * 8 + (l & 0x40) * 2 + (l & 0x30));
          wg_wait<0>();
          fence_regs(s0);
          fence_regs(s1);
          const uint4 m[4] = {ldg128(mp), ldg128(mp + 64), ldg128(mp + 256), ldg128(mp + 320)};
          add_mask(s0, s1, m);
          if (__any_sync(0xffffffffu, force != 0)) {
            subtract_row_max(s0);
            subtract_row_max(s1);
          }
        }
      }
      if constexpr (r < 4) store_v(IC<(r < 4 ? r + 2 : 0)>{});
      exp_pairs<g0(r), g0(r + 1)>(s0);
      pack_pairs<(g0(r) > LAG ? g0(r) - LAG : 0), g0(r + 1) - LAG>(s0, eb0, p0, z0);
      sched();
    });
    fence_async_proxy();
    exp_pairs<0, NB>(s1);
    pack_pairs<16 - LAG, 16>(s0, eb0, p0, z0);
    pack_pairs<0, (NB > LAG ? NB - LAG : 0)>(s1, eb1, p1, z1);
    l0.start(z0);
    sched();
    wg_barrier(j);
    side(IC<6>{});
    wg_fence();
    issue_pv<0>(o0, p0, v4);
    sched();
    static_for<4>([&](auto R) {
      constexpr int r = decltype(R)::v;
      if constexpr (r == RA) r0 = l0.finish();
      side(IC<7 + r>{});
      exp_pairs<g1(r), g1(r + 1)>(s1);
      pack_pairs<(g1(r) > LAG ? g1(r) - LAG : 0), (r < 3 ? g1(r + 1) - LAG : 16)>(s1, eb1, p1, z1);
      if (r < 3) sched();
    });
    wg_fence();
    issue_pv<1>(o1, p1, v4);
    sched();
    l1.start(z1);
    side(IC<11>{});
    wg_wait<1>();
    fence_regs(o0);
    fence_regs(p0);
    uint32_t bad = normalize<0>(o0, r0, oo);
    mbar_wait(bar + B_LFREE, par);
#pragma unroll
    for (int q = 0; q < 3; q++) st_async16(ra[q], oo[4 * q], oo[4 * q + 1], oo[4 * q + 2], oo[4 * q + 3], rb[q]);
    sched();
    r1 = l1.finish();
    side(IC<12>{});
    wg_wait<0>();
    fence_regs(o1);
    fence_regs(p1);
    if (l16 == 0) mbar_arrive(bar_o + B_VFREE);
    bad = ((bad | normalize<1>(o1, r1, oo)) & BAD_SUM) | force;
#pragma unroll
    for (int q = 3; q < 6; q++) st_async16(ra[q], oo[4 * q], oo[4 * q + 1], oo[4 * q + 2], oo[4 * q + 3], rb[q]);
    sched();
    side(IC<13>{});
    pin_rows(mr);
    masked = __any_sync(0xffffffffu, (mask_or(mr) | bad) != 0);
    if (masked && __any_sync(0xffffffffu, (bad & BAD_SUM) != 0)) {
      force |= 1;
      if ((l16 >> 4) == (uint32_t)(k >> 6)) asm volatile("red.shared.or.b32 [%0], %1;" ::"r"(sbase + OFF_FAIL + 512 * j + 128 * warp + (l16 >> 2)), "r"(1u << ((k >> 1) & 31)) : "memory");
    }
    wprev = win;
    win = wnext;
    wnext = wnn;
    wx = window(k + 5);
    k += 2;
    if (k >= nk) break;
    par ^= 1;
    mbar_wait(bar + B_TOKEN, par);
  }
  {
    const uint32_t a = sbase + OFF_FAIL + 512 * j + 128 * warp + (l16 >> 2);
    st_async4(mapa(a + 1024, peer), lds32(a), mapa(sbase + B_DONE, peer));
    __syncwarp();
    if (l16 == 0) mbar_expect_tx(sbase + B_DONE, 128);
  }
  {
    float ca[48];
    mbar_wait(sbase + B_W + 24, 0);
    gemm_phase<WO, 0, false>(ca, oo, w4, rzero, [&](auto I) {
      constexpr int s = decltype(I)::v;
      if constexpr (s == 5) { mbar_wait(bar + B_EX0, par); fetch(IC<0>{}); wg_fence(); }
      if constexpr (s == 8) { mbar_wait(bar + B_EX1, par); fetch(IC<1>{}); wg_fence(); }
    });
    wg_wait<0>();
    fence_regs(ca);
    fence_regs(oo);
    static_for<6>([&](auto PP) { store_out(PP, ca); });
    fence_async_proxy();
    __syncwarp();
    send_out(wprev, true);
  }
  if (k == nk + 1) mbar_wait(xbar_o, j ? par : par ^ 1);
  mbar_wait(sbase + B_DONE, 0);
  uint32_t failed = 0;
#pragma unroll
  for (int i = 0; i < 4; i++) {
    const uint4 f = lds128(sbase + OFF_FAIL + 512 * i + l16);
    failed |= f.x | f.y | f.z | f.w;
  }
  if (__any_sync(0xffffffffu, failed != 0)) {
    asm volatile("cp.async.bulk.wait_group 0;" ::: "memory");
    asm volatile("fence.proxy.async;" ::: "memory");
    for (int kk = 0; kk < nk; kk++) {
      uint32_t f = 0;
      for (int i = 0; i < 8; i++) f |= lds32(sbase + OFF_FAIL + 1024 * (i >> 2) + 512 * (kk & 1) + 128 * (i & 3) + 4 * (kk >> 6));
      if ((f >> ((kk >> 1) & 31)) & 1) redo_window(P, reinterpret_cast<float*>(smem_raw), window_any(kk), rank);
    }
  }
  asm volatile("cp.async.bulk.wait_group.read 0;" ::: "memory");
}

typedef CUresult (*EncodeTiledFn)(CUtensorMap*, CUtensorMapDataType, cuuint32_t, void*, const cuuint64_t*, const cuuint64_t*,
                                  const cuuint32_t*, const cuuint32_t*, CUtensorMapInterleave, CUtensorMapSwizzle,
                                  CUtensorMapL2promotion, CUtensorMapFloatOOBfill);

void encode_image_map(EncodeTiledFn fn, CUtensorMap* tm, void* ptr, uint32_t group_c, CUtensorMapSwizzle sw) {
  const cuuint64_t dims[5] = {(cuuint64_t)group_c, 2, (cuuint64_t)IMG, (cuuint64_t)IMG / 2, (cuuint64_t)(CH / group_c)};
  const cuuint64_t strides[4] = {(cuuint64_t)CH * 2, (cuuint64_t)CH * 2 * IMG, (cuuint64_t)CH * 4, (cuuint64_t)group_c * 2};
  const cuuint32_t box[5] = {group_c, 2, 4, 2, 3};
  const cuuint32_t estr[5] = {1, 1, 1, 1, 1};
  fn(tm, CU_TENSOR_MAP_DATA_TYPE_BFLOAT16, 5, ptr, dims, strides, box, estr, CU_TENSOR_MAP_INTERLEAVE_NONE, sw,
     CU_TENSOR_MAP_L2_PROMOTION_L2_128B, CU_TENSOR_MAP_FLOAT_OOB_FILL_NONE);
}
void encode_weight_map(EncodeTiledFn fn, CUtensorMap* tm, void* ptr, uint32_t cols) {
  const cuuint64_t dims[3] = {32, (cuuint64_t)CH, (cuuint64_t)(cols / 32)};
  const cuuint64_t strides[2] = {(cuuint64_t)cols * 2, 64};
  const cuuint32_t box[3] = {32, 96, 3};
  const cuuint32_t estr[3] = {1, 1, 1};
  fn(tm, CU_TENSOR_MAP_DATA_TYPE_BFLOAT16, 3, ptr, dims, strides, box, estr, CU_TENSOR_MAP_INTERLEAVE_NONE, CU_TENSOR_MAP_SWIZZLE_64B,
     CU_TENSOR_MAP_L2_PROMOTION_L2_128B, CU_TENSOR_MAP_FLOAT_OOB_FILL_NONE);
}

}

extern "C" void kernel_launch(void* const* d_in, const int* in_sizes, int n_in, void* d_out, int out_size) {
  (void)in_sizes; (void)n_in; (void)out_size;
  static int nclusters = 0;
  static EncodeTiledFn encode = nullptr;
  if (nclusters == 0) {
    cudaFuncSetAttribute(swin_attn_kernel, cudaFuncAttributeMaxDynamicSharedMemorySize, SMEM_BYTES);
    int dev = 0, sms = 0;
    cudaGetDevice(&dev);
    cudaDeviceGetAttribute(&sms, cudaDevAttrMultiProcessorCount, dev);
    nclusters = sms / 2;
    cudaLaunchConfig_t cfg = {};
    cfg.gridDim = dim3(2 * nclusters);
    cfg.blockDim = dim3(THREADS);
    cfg.dynamicSmemBytes = SMEM_BYTES;
    cudaLaunchAttribute at[1];
    at[0].id = cudaLaunchAttributeClusterDimension;
    at[0].val.clusterDim.x = 2; at[0].val.clusterDim.y = 1; at[0].val.clusterDim.z = 1;
    cfg.attrs = at; cfg.numAttrs = 1;
    int maxc = 0;
    if (cudaOccupancyMaxActiveClusters(&maxc, swin_attn_kernel, &cfg) == cudaSuccess && maxc > 0 && maxc < nclusters) nclusters = maxc;
    (void)cudaGetLastError();
    void* fn = nullptr;
    cudaDriverEntryPointQueryResult qres;
    cudaGetDriverEntryPoint("cuTensorMapEncodeTiled", &fn, cudaEnableDefault, &qres);
    encode = (EncodeTiledFn)fn;
  }
  CUtensorMap tm_x, tm_o, tm_w, tm_wo;
  encode_image_map(encode, &tm_x, d_in[0], 64, CU_TENSOR_MAP_SWIZZLE_128B);
  encode_image_map(encode, &tm_o, d_out, 32, CU_TENSOR_MAP_SWIZZLE_64B);
  encode_weight_map(encode, &tm_w, d_in[1], 3 * CH);
  encode_weight_map(encode, &tm_wo, d_in[2], CH);
  Params P;
  P.x = (const __nv_bfloat16*)d_in[0];
  P.wqkv = (const __nv_bfloat16*)d_in[1];
  P.wo = (const __nv_bfloat16*)d_in[2];
  P.rpb = (const __nv_bfloat16*)d_in[3];
  P.rp_idx = (const int*)d_in[4];
  P.mask = (const __nv_bfloat16*)d_in[5];
  P.out = (__nv_bfloat16*)d_out;
  P.wstride = nclusters;
  P.wskip = nclusters == 66 ? 16645 : 0;
  P.zero = 0;
  P.nk_min = NWIN / nclusters;
  P.nk_rem = NWIN % nclusters;
  swin_attn_kernel<<<2 * nclusters, THREADS, SMEM_BYTES, cudaStreamPerThread>>>(tm_x, tm_o, tm_w, tm_wo, P);
}
```

```cpp
#include <cuda_runtime.h>
#include <cuda_bf16.h>
#include <cuda.h>
#include <stdint.h>

namespace {

constexpr int IMG = 512, CH = 192, NWIN = 4096;
constexpr int THREADS = 256;

constexpr uint32_t OFF_X = 0;
constexpr uint32_t OFF_K = 24576;
constexpr uint32_t UB = 1536;
constexpr uint32_t OFF_V = OFF_K + 12288;
constexpr uint32_t OFF_L = OFF_V + 12288;
constexpr uint32_t OFF_W = OFF_L + 2 * 12288;
constexpr uint32_t W_HALF = 3 * 96 * 64, W_PART = 2 * W_HALF;
constexpr uint32_t WK = OFF_W, WQ = OFF_W + W_PART, WV = OFF_W + 2 * W_PART, WO = OFF_W + 3 * W_PART;
constexpr uint32_t OFF_BAR = OFF_W + 4 * W_PART;
constexpr uint32_t B_XFULL = 0;
constexpr uint32_t B_TOKEN = 32;
constexpr uint32_t B_KFREE = 40, B_VFREE = 48;
constexpr uint32_t B_EX0 = 56, B_EX1 = 64;
constexpr uint32_t B_LFREE = 72;
constexpr uint32_t B_X1 = 80;
constexpr uint32_t B_W = OFF_BAR + 256;
constexpr uint32_t B_IDX = OFF_BAR + 296;
constexpr uint32_t B_DONE = OFF_BAR + 304;
constexpr uint32_t OFF_DUMMY = OFF_BAR + 320;
constexpr uint32_t OFF_FAIL = OFF_BAR + 384;
constexpr uint32_t OFF_TAB = OFF_FAIL + 2048;
constexpr uint32_t OFF_END = OFF_TAB + 1024;
constexpr uint32_t SMEM_BYTES = OFF_END;

constexpr float LOG2E = 1.4426950408889634f;
constexpr float SCALE = 0.14433756729740643f;

__device__ __forceinline__ uint32_t smem_u32(const void* p) { return (uint32_t)__cvta_generic_to_shared(p); }
__device__ __forceinline__ void wg_fence() { asm volatile("wgmma.fence.sync.aligned;" ::: "memory"); }
__device__ __forceinline__ void wg_commit() { asm volatile("wgmma.commit_group.sync.aligned;" ::: "memory"); }
template <int N> __device__ __forceinline__ void wg_wait() { asm volatile("wgmma.wait_group.sync.aligned %0;" ::"n"(N) : "memory"); }
template <int N> __device__ __forceinline__ void fence_regs(float (&d)[N]) {
#pragma unroll
  for (int i = 0; i < N; i++) asm volatile("" : "+f"(d[i])::"memory");
}
template <int N> __device__ __forceinline__ void fence_regs(uint32_t (&d)[N]) {
#pragma unroll
  for (int i = 0; i < N; i++) asm volatile("" : "+r"(d[i])::"memory");
}
__device__ __forceinline__ bool elect_one() {
  uint32_t pred;
  asm volatile("{\n.reg .pred p;\nelect.sync _|p, 0xffffffff;\nselp.u32 %0, 1, 0, p;\n}\n" : "=r"(pred));
  return pred != 0;
}
__device__ __forceinline__ uint32_t pack_bf16(float lo, float hi) {
  uint32_t r;
  asm("cvt.rn.bf16x2.f32 %0, %1, %2;" : "=r"(r) : "f"(hi), "f"(lo));
  return r;
}
__device__ __forceinline__ float bf_lo(uint32_t v) { return __uint_as_float(v << 16); }
__device__ __forceinline__ float bf_hi(uint32_t v) { return __uint_as_float(v & 0xffff0000u); }
__device__ __forceinline__ float ex2(float x) {
  float y;
  asm("ex2.approx.ftz.f32 %0, %1;" : "=f"(y) : "f"(x));
  return y;
}
__device__ __forceinline__ uint32_t hadd2(uint32_t a, uint32_t b) {
  uint32_t r;
  asm("add.rn.bf16x2 %0, %1, %2;" : "=r"(r) : "r"(a), "r"(b));
  return r;
}
__device__ __forceinline__ uint32_t hmul2(uint32_t a, uint32_t b) {
  uint32_t r;
  asm("mul.rn.bf16x2 %0, %1, %2;" : "=r"(r) : "r"(a), "r"(b));
  return r;
}
__device__ __forceinline__ uint32_t dup_lo(uint32_t a) {
  uint32_t r;
  asm("{\n.reg .b16 l, h;\nmov.b32 {l, h}, %1;\nmov.b32 %0, {l, l};\n}\n" : "=r"(r) : "r"(a));
  return r;
}
__device__ __forceinline__ uint32_t dup_hi(uint32_t a) {
  uint32_t r;
  asm("{\n.reg .b16 l, h;\nmov.b32 {l, h}, %1;\nmov.b32 %0, {h, h};\n}\n" : "=r"(r) : "r"(a));
  return r;
}
__device__ __forceinline__ float rcp_approx(float x) {
  float y;
  asm("rcp.approx.ftz.f32 %0, %1;" : "=f"(y) : "f"(x));
  return y;
}
__device__ __forceinline__ uint4 ldg128(const void* p) {
  uint4 v;
  asm volatile("ld.global.L1::evict_normal.v4.u32 {%0,%1,%2,%3}, [%4];" : "=r"(v.x), "=r"(v.y), "=r"(v.z), "=r"(v.w) : "l"(p) : "memory");
  return v;
}
__device__ __forceinline__ void prefetch_l2(const void* p, uint32_t bytes) {
  asm volatile("cp.async.bulk.prefetch.L2.global [%0], %1;" ::"l"(p), "r"(bytes) : "memory");
}
__device__ __forceinline__ uint4 lds128(uint32_t addr) {
  uint4 v;
  asm volatile("ld.shared.v4.u32 {%0,%1,%2,%3}, [%4];" : "=r"(v.x), "=r"(v.y), "=r"(v.z), "=r"(v.w) : "r"(addr) : "memory");
  return v;
}
__device__ __forceinline__ uint4 lds128v(uint32_t addr) {
  uint4 v;
  asm volatile("ld.volatile.shared.v4.u32 {%0,%1,%2,%3}, [%4];" : "=r"(v.x), "=r"(v.y), "=r"(v.z), "=r"(v.w) : "r"(addr) : "memory");
  return v;
}
__device__ __forceinline__ uint32_t lds32(uint32_t addr) {
  uint32_t v;
  asm volatile("ld.shared.u32 %0, [%1];" : "=r"(v) : "r"(addr) : "memory");
  return v;
}
__device__ __forceinline__ void stmatrix_x4(uint32_t addr, uint32_t a, uint32_t b, uint32_t c, uint32_t d) {
  asm volatile("stmatrix.sync.aligned.m8n8.x4.shared.b16 [%0], {%1,%2,%3,%4};" ::"r"(addr), "r"(a), "r"(b), "r"(c), "r"(d) : "memory");
}
__device__ __forceinline__ void ldmatrix_x4(uint32_t addr, uint32_t& a, uint32_t& b, uint32_t& c, uint32_t& d) {
  asm volatile("ldmatrix.sync.aligned.m8n8.x4.shared.b16 {%0,%1,%2,%3}, [%4];" : "=r"(a), "=r"(b), "=r"(c), "=r"(d) : "r"(addr) : "memory");
}
__device__ __forceinline__ void fence_async_proxy() {
  asm volatile("fence.proxy.async.shared::cta;" ::: "memory");
}
__device__ __forceinline__ void wg_barrier(int j) { asm volatile("bar.sync %0, 128;" ::"r"(1 + j) : "memory"); }
__device__ __forceinline__ void cluster_wait() { asm volatile("barrier.cluster.wait.acquire.aligned;" ::: "memory"); }
__device__ __forceinline__ uint32_t mapa(uint32_t a, uint32_t rank) {
  uint32_t o;
  asm("mapa.shared::cluster.u32 %0, %1, %2;" : "=r"(o) : "r"(a), "r"(rank));
  return o;
}
__device__ __forceinline__ void mbar_init(uint32_t a, uint32_t cnt) { asm volatile("mbarrier.init.shared::cta.b64 [%0], %1;" ::"r"(a), "r"(cnt) : "memory"); }
__device__ __forceinline__ void mbar_expect_tx(uint32_t a, uint32_t tx) {
  asm volatile("mbarrier.arrive.expect_tx.shared::cta.b64 _, [%0], %1;" ::"r"(a), "r"(tx) : "memory");
}
__device__ __forceinline__ void mbar_arrive(uint32_t a) { asm volatile("mbarrier.arrive.shared::cta.b64 _, [%0];" ::"r"(a) : "memory"); }
__device__ __forceinline__ void mbar_arrive4(uint32_t a) { asm volatile("mbarrier.arrive.shared::cta.b64 _, [%0], 4;" ::"r"(a) : "memory"); }
__device__ __forceinline__ uint32_t uniform(uint32_t v) { return __shfl_sync(0xffffffffu, v, 0); }
__device__ __forceinline__ void mbar_arrive_remote_relaxed(uint32_t a) {
  asm volatile("mbarrier.arrive.relaxed.cluster.shared::cluster.b64 _, [%0];" ::"r"(a) : "memory");
}
__device__ __forceinline__ void mbar_wait(uint32_t a, uint32_t parity) {
  asm volatile(
      "{\n.reg .pred p;\n.reg .u32 n;\n"
      "mbarrier.try_wait.parity.shared::cta.b64 p, [%0], %1;\n"
      "@p bra WAIT_DONE;\n"
      "mov.u32 n, 0;\n"
      "WAIT_LOOP:\n"
      "add.u32 n, n, 1;\n"
      "setp.gt.u32 p, n, 50000000;\n"
      "@p trap;\n"
      "mbarrier.try_wait.parity.shared::cta.b64 p, [%0], %1;\n"
      "@!p bra WAIT_LOOP;\n"
      "WAIT_DONE:\n}\n" ::"r"(a), "r"(parity) : "memory");
}
__device__ __forceinline__ bool mbar_test(uint32_t a, uint32_t parity) {
  uint32_t ok;
  asm volatile("{\n.reg .pred p;\nmbarrier.test_wait.parity.shared::cta.b64 p, [%1], %2;\nselp.u32 %0, 1, 0, p;\n}\n" : "=r"(ok) : "r"(a), "r"(parity) : "memory");
  return ok != 0;
}
__device__ __forceinline__ uint32_t hfma2(uint32_t a, uint32_t b, uint32_t c) {
  uint32_t r;
  asm("fma.rn.bf16x2 %0, %1, %2, %3;" : "=r"(r) : "r"(a), "r"(b), "r"(c));
  return r;
}
__device__ __forceinline__ void st_async16(uint32_t raddr, uint32_t a, uint32_t b, uint32_t c, uint32_t d, uint32_t rbar) {
  asm volatile("st.async.weak.shared::cluster.mbarrier::complete_tx::bytes.v4.b32 [%0], {%1,%2,%3,%4}, [%5];" ::"r"(raddr),
               "r"(a), "r"(b), "r"(c), "r"(d), "r"(rbar) : "memory");
}

__device__ __forceinline__ void st_async4(uint32_t raddr, uint32_t v, uint32_t rbar) {
  asm volatile("st.async.weak.shared::cluster.mbarrier::complete_tx::bytes.b32 [%0], %1, [%2];" ::"r"(raddr), "r"(v), "r"(rbar) : "memory");
}
__device__ __forceinline__ void sts128(uint32_t addr, uint4 v) {
  asm volatile("st.shared.v4.u32 [%0], {%1,%2,%3,%4};" ::"r"(addr), "r"(v.x), "r"(v.y), "r"(v.z), "r"(v.w) : "memory");
}
__device__ __forceinline__ void bulk_load(uint32_t dst, const void* src, uint32_t bytes, uint32_t bar) {
  asm volatile("cp.async.bulk.shared::cta.global.mbarrier::complete_tx::bytes [%0], [%1], %2, [%3];" ::"r"(dst), "l"(src),
               "r"(bytes), "r"(bar) : "memory");
}
__device__ __forceinline__ void tma_load3(uint32_t dst, const CUtensorMap* tm, int c1, int c2, uint32_t bar) {
  asm volatile("cp.async.bulk.tensor.3d.shared::cta.global.tile.mbarrier::complete_tx::bytes [%0], [%1, {0, %2, %3}], [%4];" ::"r"(dst),
               "l"(tm), "r"(c1), "r"(c2), "r"(bar) : "memory");
}
__device__ __forceinline__ void tma_load5(uint32_t dst, const CUtensorMap* tm, int c2, int c3, uint32_t bar) {
  asm volatile("cp.async.bulk.tensor.5d.shared::cta.global.tile.mbarrier::complete_tx::bytes [%0], [%1, {0, 0, %2, %3, 0}], [%4];" ::"r"(dst),
               "l"(tm), "r"(c2), "r"(c3), "r"(bar) : "memory");
}
__device__ __forceinline__ void tma_store5(const CUtensorMap* tm, int c2, int c3, int c4, uint32_t src, uint64_t policy) {
  asm volatile("cp.async.bulk.tensor.5d.global.shared::cta.tile.bulk_group.L2::cache_hint [%0, {0, 0, %1, %2, %3}], [%4], %5;" ::"l"(tm),
               "r"(c2), "r"(c3), "r"(c4), "r"(src), "l"(policy) : "memory");
}
__device__ __forceinline__ void sched_barrier(uint32_t& t, uint32_t zero) {
  asm volatile("{\n.reg .pred p;\nsetp.ne.u32 p, %1, 0;\n@p mov.u32 %0, %%clock;\n}\n" : "+r"(t) : "r"(zero) : "memory");
}

__device__ __forceinline__ void wgmma_n48_a(float (&d)[24], uint32_t a0, uint32_t a1, uint32_t a2, uint32_t a3, uint64_t db) {
  asm volatile("{\n.reg .pred p;\nsetp.ne.b32 p, 1, 0;\n"
      "wgmma.mma_async.sync.aligned.m64n48k16.f32.bf16.bf16 "
      "{%0,%1,%2,%3,%4,%5,%6,%7,%8,%9,%10,%11,%12,%13,%14,%15,"
      "%16,%17,%18,%19,%20,%21,%22,%23}, "
      "{%24,%25,%26,%27}, %28, p, 1, 1, 1;\n}\n"
      : "+f"(d[0]), "+f"(d[1]), "+f"(d[2]), "+f"(d[3]), "+f"(d[4]), "+f"(d[5]), "+f"(d[6]), "+f"(d[7]),
        "+f"(d[8]), "+f"(d[9]), "+f"(d[10]), "+f"(d[11]), "+f"(d[12]), "+f"(d[13]), "+f"(d[14]), "+f"(d[15]),
        "+f"(d[16]), "+f"(d[17]), "+f"(d[18]), "+f"(d[19]), "+f"(d[20]), "+f"(d[21]), "+f"(d[22]), "+f"(d[23])
      : "r"(a0), "r"(a1), "r"(a2), "r"(a3), "l"(db));
}
__device__ __forceinline__ void wgmma_n48_z(float (&d)[24], uint32_t a0, uint32_t a1, uint32_t a2, uint32_t a3, uint64_t db) {
  asm volatile("{\n.reg .pred p;\nsetp.ne.b32 p, 0, 0;\n"
      "wgmma.mma_async.sync.aligned.m64n48k16.f32.bf16.bf16 "
      "{%0,%1,%2,%3,%4,%5,%6,%7,%8,%9,%10,%11,%12,%13,%14,%15,"
      "%16,%17,%18,%19,%20,%21,%22,%23}, "
      "{%24,%25,%26,%27}, %28, p, 1, 1, 1;\n}\n"
      : "=f"(d[0]), "=f"(d[1]), "=f"(d[2]), "=f"(d[3]), "=f"(d[4]), "=f"(d[5]), "=f"(d[6]), "=f"(d[7]),
        "=f"(d[8]), "=f"(d[9]), "=f"(d[10]), "=f"(d[11]), "=f"(d[12]), "=f"(d[13]), "=f"(d[14]), "=f"(d[15]),
        "=f"(d[16]), "=f"(d[17]), "=f"(d[18]), "=f"(d[19]), "=f"(d[20]), "=f"(d[21]), "=f"(d[22]), "=f"(d[23])
      : "r"(a0), "r"(a1), "r"(a2), "r"(a3), "l"(db));
}
__device__ __forceinline__ void wgmma_n96_a(float (&d)[48], uint32_t a0, uint32_t a1, uint32_t a2, uint32_t a3, uint64_t db) {
  asm volatile("{\n.reg .pred p;\nsetp.ne.b32 p, 1, 0;\n"
      "wgmma.mma_async.sync.aligned.m64n96k16.f32.bf16.bf16 "
      "{%0,%1,%2,%3,%4,%5,%6,%7,%8,%9,%10,%11,%12,%13,%14,%15,"
      "%16,%17,%18,%19,%20,%21,%22,%23,%24,%25,%26,%27,%28,%29,%30,%31,"
      "%32,%33,%34,%35,%36,%37,%38,%39,%40,%41,%42,%43,%44,%45,%46,%47}, "
      "{%48,%49,%50,%51}, %52, p, 1, 1, 1;\n}\n"
      : "+f"(d[0]), "+f"(d[1]), "+f"(d[2]), "+f"(d[3]), "+f"(d[4]), "+f"(d[5]), "+f"(d[6]), "+f"(d[7]),
        "+f"(d[8]), "+f"(d[9]), "+f"(d[10]), "+f"(d[11]), "+f"(d[12]), "+f"(d[13]), "+f"(d[14]), "+f"(d[15]),
        "+f"(d[16]), "+f"(d[17]), "+f"(d[18]), "+f"(d[19]), "+f"(d[20]), "+f"(d[21]), "+f"(d[22]), "+f"(d[23]),
        "+f"(d[24]), "+f"(d[25]), "+f"(d[26]), "+f"(d[27]), "+f"(d[28]), "+f"(d[29]), "+f"(d[30]), "+f"(d[31]),
        "+f"(d[32]), "+f"(d[33]), "+f"(d[34]), "+f"(d[35]), "+f"(d[36]), "+f"(d[37]), "+f"(d[38]), "+f"(d[39]),
        "+f"(d[40]), "+f"(d[41]), "+f"(d[42]), "+f"(d[43]), "+f"(d[44]), "+f"(d[45]), "+f"(d[46]), "+f"(d[47])
      : "r"(a0), "r"(a1), "r"(a2), "r"(a3), "l"(db));
}
__device__ __forceinline__ void wgmma_n96_z(float (&d)[48], uint32_t a0, uint32_t a1, uint32_t a2, uint32_t a3, uint64_t db) {
  asm volatile("{\n.reg .pred p;\nsetp.ne.b32 p, 0, 0;\n"
      "wgmma.mma_async.sync.aligned.m64n96k16.f32.bf16.bf16 "
      "{%0,%1,%2,%3,%4,%5,%6,%7,%8,%9,%10,%11,%12,%13,%14,%15,"
      "%16,%17,%18,%19,%20,%21,%22,%23,%24,%25,%26,%27,%28,%29,%30,%31,"
      "%32,%33,%34,%35,%36,%37,%38,%39,%40,%41,%42,%43,%44,%45,%46,%47}, "
      "{%48,%49,%50,%51}, %52, p, 1, 1, 1;\n}\n"
      : "=f"(d[0]), "=f"(d[1]), "=f"(d[2]), "=f"(d[3]), "=f"(d[4]), "=f"(d[5]), "=f"(d[6]), "=f"(d[7]),
        "=f"(d[8]), "=f"(d[9]), "=f"(d[10]), "=f"(d[11]), "=f"(d[12]), "=f"(d[13]), "=f"(d[14]), "=f"(d[15]),
        "=f"(d[16]), "=f"(d[17]), "=f"(d[18]), "=f"(d[19]), "=f"(d[20]), "=f"(d[21]), "=f"(d[22]), "=f"(d[23]),
        "=f"(d[24]), "=f"(d[25]), "=f"(d[26]), "=f"(d[27]), "=f"(d[28]), "=f"(d[29]), "=f"(d[30]), "=f"(d[31]),
        "=f"(d[32]), "=f"(d[33]), "=f"(d[34]), "=f"(d[35]), "=f"(d[36]), "=f"(d[37]), "=f"(d[38]), "=f"(d[39]),
        "=f"(d[40]), "=f"(d[41]), "=f"(d[42]), "=f"(d[43]), "=f"(d[44]), "=f"(d[45]), "=f"(d[46]), "=f"(d[47])
      : "r"(a0), "r"(a1), "r"(a2), "r"(a3), "l"(db));
}
__device__ __forceinline__ void wgmma_n96_p(float (&d)[48], uint32_t a0, uint32_t a1, uint32_t a2, uint32_t a3, uint64_t db, uint32_t acc) {
  asm volatile("{\n.reg .pred p;\nsetp.ne.b32 p, %53, 0;\n"
      "wgmma.mma_async.sync.aligned.m64n96k16.f32.bf16.bf16 "
      "{%0,%1,%2,%3,%4,%5,%6,%7,%8,%9,%10,%11,%12,%13,%14,%15,"
      "%16,%17,%18,%19,%20,%21,%22,%23,%24,%25,%26,%27,%28,%29,%30,%31,"
      "%32,%33,%34,%35,%36,%37,%38,%39,%40,%41,%42,%43,%44,%45,%46,%47}, "
      "{%48,%49,%50,%51}, %52, p, 1, 1, 1;\n}\n"
      : "+f"(d[0]), "+f"(d[1]), "+f"(d[2]), "+f"(d[3]), "+f"(d[4]), "+f"(d[5]), "+f"(d[6]), "+f"(d[7]),
        "+f"(d[8]), "+f"(d[9]), "+f"(d[10]), "+f"(d[11]), "+f"(d[12]), "+f"(d[13]), "+f"(d[14]), "+f"(d[15]),
        "+f"(d[16]), "+f"(d[17]), "+f"(d[18]), "+f"(d[19]), "+f"(d[20]), "+f"(d[21]), "+f"(d[22]), "+f"(d[23]),
        "+f"(d[24]), "+f"(d[25]), "+f"(d[26]), "+f"(d[27]), "+f"(d[28]), "+f"(d[29]), "+f"(d[30]), "+f"(d[31]),
        "+f"(d[32]), "+f"(d[33]), "+f"(d[34]), "+f"(d[35]), "+f"(d[36]), "+f"(d[37]), "+f"(d[38]), "+f"(d[39]),
        "+f"(d[40]), "+f"(d[41]), "+f"(d[42]), "+f"(d[43]), "+f"(d[44]), "+f"(d[45]), "+f"(d[46]), "+f"(d[47])
      : "r"(a0), "r"(a1), "r"(a2), "r"(a3), "l"(db), "r"(acc));
}
__device__ __forceinline__ void wgmma_n64_a(float (&d)[32], uint32_t a0, uint32_t a1, uint32_t a2, uint32_t a3, uint64_t db) {
  asm volatile("{\n.reg .pred p;\nsetp.ne.b32 p, 1, 0;\n"
      "wgmma.mma_async.sync.aligned.m64n64k16.f32.bf16.bf16 "
      "{%0,%1,%2,%3,%4,%5,%6,%7,%8,%9,%10,%11,%12,%13,%14,%15,"
      "%16,%17,%18,%19,%20,%21,%22,%23,%24,%25,%26,%27,%28,%29,%30,%31}, "
      "{%32,%33,%34,%35}, %36, p, 1, 1, 0;\n}\n"
      : "+f"(d[0]), "+f"(d[1]), "+f"(d[2]), "+f"(d[3]), "+f"(d[4]), "+f"(d[5]), "+f"(d[6]), "+f"(d[7]),
        "+f"(d[8]), "+f"(d[9]), "+f"(d[10]), "+f"(d[11]), "+f"(d[12]), "+f"(d[13]), "+f"(d[14]), "+f"(d[15]),
        "+f"(d[16]), "+f"(d[17]), "+f"(d[18]), "+f"(d[19]), "+f"(d[20]), "+f"(d[21]), "+f"(d[22]), "+f"(d[23]),
        "+f"(d[24]), "+f"(d[25]), "+f"(d[26]), "+f"(d[27]), "+f"(d[28]), "+f"(d[29]), "+f"(d[30]), "+f"(d[31])
      : "r"(a0), "r"(a1), "r"(a2), "r"(a3), "l"(db));
}
__device__ __forceinline__ void wgmma_n64_z(float (&d)[32], uint32_t a0, uint32_t a1, uint32_t a2, uint32_t a3, uint64_t db) {
  asm volatile("{\n.reg .pred p;\nsetp.ne.b32 p, 0, 0;\n"
      "wgmma.mma_async.sync.aligned.m64n64k16.f32.bf16.bf16 "
      "{%0,%1,%2,%3,%4,%5,%6,%7,%8,%9,%10,%11,%12,%13,%14,%15,"
      "%16,%17,%18,%19,%20,%21,%22,%23,%24,%25,%26,%27,%28,%29,%30,%31}, "
      "{%32,%33,%34,%35}, %36, p, 1, 1, 0;\n}\n"
      : "=f"(d[0]), "=f"(d[1]), "=f"(d[2]), "=f"(d[3]), "=f"(d[4]), "=f"(d[5]), "=f"(d[6]), "=f"(d[7]),
        "=f"(d[8]), "=f"(d[9]), "=f"(d[10]), "=f"(d[11]), "=f"(d[12]), "=f"(d[13]), "=f"(d[14]), "=f"(d[15]),
        "=f"(d[16]), "=f"(d[17]), "=f"(d[18]), "=f"(d[19]), "=f"(d[20]), "=f"(d[21]), "=f"(d[22]), "=f"(d[23]),
        "=f"(d[24]), "=f"(d[25]), "=f"(d[26]), "=f"(d[27]), "=f"(d[28]), "=f"(d[29]), "=f"(d[30]), "=f"(d[31])
      : "r"(a0), "r"(a1), "r"(a2), "r"(a3), "l"(db));
}

template <uint32_t OFF, uint32_t LBO>
__device__ __forceinline__ uint64_t desc_at(uint64_t base) {
  return base + (uint64_t)((OFF >> 4) + ((LBO >> 4) << 16));
}
template <uint32_t SBO, uint32_t SWIZZLE = 0>
__device__ __forceinline__ uint64_t desc_base(uint32_t addr4) {
  return ((uint64_t)SWIZZLE << 62) | ((uint64_t)(SBO >> 4) << 32) | (uint64_t)addr4;
}
__device__ __forceinline__ uint64_t pin(uint64_t v) {
  asm volatile("" : "+l"(v));
  return v;
}
template <int I> struct IC { static constexpr int v = I; };
template <int N, class F> __device__ __forceinline__ void static_for(F&& f) {
  if constexpr (N > 0) { static_for<N - 1>(f); f(IC<N - 1>{}); }
}

__device__ __forceinline__ void quad_origin(int win, int w, bool valid, int& row, int& col2) {
  col2 = (4 * (win & 63) + 2 + 2 * (w & 1)) & (IMG / 2 - 1);
  row = (8 * (win >> 6) + 4 + 4 * (w >> 1)) & (IMG - 1);
  if (!valid) row = IMG;
}
__device__ __forceinline__ void load_tile(uint32_t dst, int warp, int win, bool valid, uint32_t xbar, const CUtensorMap* tm_x) {
  int row, col2;
  quad_origin(win, warp, valid, row, col2);
  if (elect_one()) {
    mbar_expect_tx(xbar, 6144);
    tma_load5(dst, tm_x, row, col2, xbar);
  }
}
template <int S>
__device__ __forceinline__ void read_x(uint32_t (&xa)[48], const uint32_t (&xaddr)[4]) {
  ldmatrix_x4(xaddr[S & 3] + (S >> 2) * 2048, xa[4 * S], xa[4 * S + 1], xa[4 * S + 2], xa[4 * S + 3]);
}
__device__ __forceinline__ void reads_done(uint32_t last, uint32_t dummy_addr) {
  asm volatile("{\n.reg .pred p;\nsetp.eq.u32 p, %0, 0x7fc1fc17;\n@p st.shared.u32 [%1], %0;\n}\n" ::"r"(last), "r"(dummy_addr) : "memory");
}
template <int P>
__device__ __forceinline__ void store_chunk(uint32_t addr, float (&d)[48]) {
  stmatrix_x4(addr, pack_bf16(d[8 * P + 0], d[8 * P + 1]), pack_bf16(d[8 * P + 2], d[8 * P + 3]),
              pack_bf16(d[8 * P + 4], d[8 * P + 5]), pack_bf16(d[8 * P + 6], d[8 * P + 7]));
}
constexpr int IDLE = -100;
template <uint32_t WOFF, int H, bool TIED, class F>
__device__ __forceinline__ void gemm_phase(float (&run)[48], uint32_t (&x)[48], uint64_t w4, uint32_t rzero, F&& after) {
  wg_fence();
  static_for<12>([&](auto I) {
    constexpr int s = decltype(I)::v;
    const uint64_t d = desc_at<WOFF + (s / 6) * W_HALF + (s % 6) * 1024, 6144>(pin(w4));
    if constexpr (s == 0 && TIED) wgmma_n96_p(run, x[0], x[1], x[2], x[3], d, rzero);
    else if constexpr (s == 0) wgmma_n96_z(run, x[0], x[1], x[2], x[3], d);
    else wgmma_n96_a(run, x[4 * s], x[4 * s + 1], x[4 * s + 2], x[4 * s + 3], d);
    if constexpr (s == H - 1 || s == 11) wg_commit();
    if constexpr (s == H - 1) { after(IC<IDLE>{}); wg_wait<1>(); }
    after(I);
  });
}
template <int H>
__device__ __forceinline__ void issue_s(float (&s)[32], uint32_t (&q)[24], uint64_t k4_) {
  const uint64_t k4 = pin(k4_);
  static_for<3>([&](auto I) {
    constexpr int k = decltype(I)::v, i = 12 * H + 4 * k;
    const uint64_t d = desc_at<OFF_K + H * 768 + k * 256, 128>(k4);
    if constexpr (k == 0) wgmma_n64_z(s, q[i], q[i + 1], q[i + 2], q[i + 3], d);
    else wgmma_n64_a(s, q[i], q[i + 1], q[i + 2], q[i + 3], d);
  });
  wg_commit();
}
__device__ __forceinline__ const uint8_t* offset_ptr(const uint8_t* base, uint32_t off) {
  const uint8_t* r;
  asm volatile("{\n.reg .u64 o;\ncvt.u64.u32 o, %2;\nadd.u64 %0, %1, o;\n}\n" : "=l"(r) : "l"(base), "r"(off));
  return r;
}
struct MaskRows { uint4 a, b, c, d; };
__device__ __forceinline__ MaskRows mask_load(const uint8_t* mp) {
  MaskRows r;
  r.a = ldg128(mp); r.b = ldg128(mp + 1024); r.c = ldg128(mp + 2048); r.d = ldg128(mp + 3072);
  return r;
}
__device__ __forceinline__ void pin_rows(MaskRows& r) {
  asm volatile("" : "+r"(r.a.x), "+r"(r.a.y), "+r"(r.a.z), "+r"(r.a.w), "+r"(r.b.x), "+r"(r.b.y), "+r"(r.b.z), "+r"(r.b.w),
                    "+r"(r.c.x), "+r"(r.c.y), "+r"(r.c.z), "+r"(r.c.w), "+r"(r.d.x), "+r"(r.d.y), "+r"(r.d.z), "+r"(r.d.w)::"memory");
}
__device__ __forceinline__ uint32_t mask_or(const MaskRows& r) {
  return (r.a.x | r.a.y | r.a.z | r.a.w) | (r.b.x | r.b.y | r.b.z | r.b.w) | (r.c.x | r.c.y | r.c.z | r.c.w) | (r.d.x | r.d.y | r.d.z | r.d.w);
}
__device__ __forceinline__ void add_mask(float (&s0)[32], float (&s1)[32], const uint4 (&m)[4]) {
#pragma unroll
  for (int t = 0; t < 2; t++) {
#pragma unroll
    for (int b = 0; b < 8; b++) {
      const uint4 u = m[2 * t + (b >> 2)];
      const uint32_t v = (b & 3) == 0 ? u.x : (b & 3) == 1 ? u.y : (b & 3) == 2 ? u.z : u.w;
      const int i = 4 * b + 2 * t;
      s0[i] = fmaf(bf_lo(v), LOG2E, s0[i]); s0[i + 1] = fmaf(bf_hi(v), LOG2E, s0[i + 1]);
      s1[i] = fmaf(bf_lo(v), LOG2E, s1[i]); s1[i + 1] = fmaf(bf_hi(v), LOG2E, s1[i + 1]);
    }
  }
}
__device__ __forceinline__ void subtract_row_max(float (&s)[32]) {
#pragma unroll
  for (int t = 0; t < 2; t++) {
    float x = -INFINITY;
#pragma unroll
    for (int b = 0; b < 8; b++) x = fmaxf(x, fmaxf(s[4 * b + 2 * t], s[4 * b + 2 * t + 1]));
    x = fmaxf(x, __shfl_xor_sync(0xffffffffu, x, 1));
    x = fmaxf(x, __shfl_xor_sync(0xffffffffu, x, 2));
#pragma unroll
    for (int b = 0; b < 8; b++) { s[4 * b + 2 * t] -= x; s[4 * b + 2 * t + 1] -= x; }
  }
}
template <int I0, int I1>
__device__ __forceinline__ void exp_pairs(float (&s)[32]) {
#pragma unroll
  for (int i = 2 * I0; i < 2 * I1; i++) {
    asm volatile("" : "+f"(s[i])::"memory");
    s[i] = ex2(s[i]);
    asm volatile("" : "+f"(s[i])::"memory");
  }
}
template <int I0, int I1>
__device__ __forceinline__ void pack_pairs(float (&s)[32], const uint32_t (&eb)[16], uint32_t (&p)[16], uint32_t (&z)[6]) {
#pragma unroll
  for (int i = I0; i < I1; i++) {
    asm volatile("" : "+f"(s[2 * i]), "+f"(s[2 * i + 1])::"memory");
    p[i] = hmul2(pack_bf16(s[2 * i], s[2 * i + 1]), eb[i]);
    asm volatile("" : "+r"(p[i])::"memory");
    const int b = i >> 1, t = i & 1;
    if (b & 1) {
      uint32_t v = hadd2(p[i - 2], p[i]);
      if (b & 2) v = hadd2(z[4 + t], v);
      if (b == 7) v = hadd2(z[2 + t], v);
      uint32_t& dst = z[(b == 7 ? 0 : (b & 2) ? 2 : 4) + t];
      dst = v;
      asm volatile("" : "+r"(dst)::"memory");
    }
  }
}
struct RowSums {
  uint32_t a, b, c, d;
  __device__ __forceinline__ void start(const uint32_t (&z)[6]) {
    a = hadd2(__byte_perm(z[0], z[1], 0x5410), __byte_perm(z[0], z[1], 0x7632));
    b = __shfl_xor_sync(0xffffffffu, a, 1);
    c = __shfl_xor_sync(0xffffffffu, a, 2);
    d = __shfl_xor_sync(0xffffffffu, a, 3);
  }
  __device__ __forceinline__ uint32_t finish() {
    asm volatile("" : "+r"(a), "+r"(b), "+r"(c), "+r"(d)::"memory");
    const uint32_t x = hadd2(a, b), y = hadd2(c, d);
    return pack_bf16(rcp_approx(bf_lo(x) + bf_lo(y)), rcp_approx(bf_hi(x) + bf_hi(y)));
  }
};
template <int H>
__device__ __forceinline__ void issue_pv(float (&oacc)[24], uint32_t (&p)[16], uint64_t v4_) {
  const uint64_t v4 = pin(v4_);
  static_for<4>([&](auto I) {
    constexpr int k = decltype(I)::v;
    const uint64_t d = desc_at<OFF_V + H * 6144 + k * 256, 128>(v4);
    if constexpr (k == 0) wgmma_n48_z(oacc, p[0], p[1], p[2], p[3], d);
    else wgmma_n48_a(oacc, p[4 * k], p[4 * k + 1], p[4 * k + 2], p[4 * k + 3], d);
  });
  wg_commit();
}
constexpr uint32_t BAD_SUM = 0xE000E000u;
template <int H>
__device__ __forceinline__ uint32_t normalize(float (&oacc)[24], uint32_t r, uint32_t (&o)[48]) {
  const uint32_t ra = dup_lo(r), rb = dup_hi(r);
#pragma unroll
  for (int k = 0; k < 12; k++) o[12 * H + k] = hmul2(pack_bf16(oacc[2 * k], oacc[2 * k + 1]), (k & 1) ? rb : ra);
  return r - 0x2F802F80u;
}

constexpr int MAX_CLUSTERS = 72;
struct Plan { uint32_t w01, w23, w4n; int wbase; };
struct Params {
  const __nv_bfloat16 *x, *wqkv, *wo, *rpb;
  const int* rp_idx;
  const __nv_bfloat16* mask;
  __nv_bfloat16* out;
  int wstride, wskip, zero;
  __align__(16) Plan plan[MAX_CLUSTERS];
};
__device__ __forceinline__ float round_bf16(float v) { return __bfloat162float(__float2bfloat16(v)); }
__device__ __forceinline__ void redo_window(const Params& P, float* sm, int win, int rank) {
  float* xt = sm;
  float* qkv = sm + 192 * 64;
  const int tid = threadIdx.x;
  auto pixel = [&](int n) { return (size_t)(((8 * (win >> 6) + (n >> 3) + 4) & (IMG - 1)) * IMG + ((8 * (win & 63) + (n & 7) + 4) & (IMG - 1))) * CH; };
  auto gemm = [&](const __nv_bfloat16* w, int ldw, int ncols, auto&& put) {
    for (int e = tid; e < 4 * ncols; e += THREADS) {
      const int g = e / ncols, d = e - g * ncols;
      float acc[16];
#pragma unroll
      for (int i = 0; i < 16; i++) acc[i] = 0.f;
      for (int c = 0; c < CH; c++) {
        const float wv = __bfloat162float(w[c * ldw + d]);
#pragma unroll
        for (int i = 0; i < 16; i++) acc[i] = fmaf(xt[c * 64 + 16 * g + i], wv, acc[i]);
      }
#pragma unroll
      for (int i = 0; i < 16; i++) put(16 * g + i, d, acc[i]);
    }
  };
  __syncthreads();
  for (int e = tid; e < 64 * CH; e += THREADS) xt[(e % CH) * 64 + e / CH] = __bfloat162float(P.x[pixel(e / CH) + e % CH]);
  __syncthreads();
  gemm(P.wqkv, 3 * CH, 3 * CH, [&](int n, int d, float v) { qkv[n * 577 + d] = round_bf16(v); });
  __syncthreads();
  {
    const int n = tid & 63, h = tid >> 6;
    auto logit = [&](int m) {
      float s = 0.f;
      for (int d = 0; d < 48; d++) s = fmaf(qkv[n * 577 + 48 * h + d], qkv[m * 577 + CH + 48 * h + d], s);
      return s * SCALE + __bfloat162float(P.rpb[P.rp_idx[n * 64 + m] * 4 + h]) + __bfloat162float(P.mask[(size_t)win * 4096 + n * 64 + m]);
    };
    float mx = -INFINITY, sum = 0.f, o[48];
    for (int m = 0; m < 64; m++) mx = fmaxf(mx, logit(m));
#pragma unroll
    for (int d = 0; d < 48; d++) o[d] = 0.f;
    for (int m = 0; m < 64; m++) {
      const float p = expf(logit(m) - mx);
      sum += p;
#pragma unroll
      for (int d = 0; d < 48; d++) o[d] = fmaf(p, qkv[m * 577 + 2 * CH + 48 * h + d], o[d]);
    }
#pragma unroll
    for (int d = 0; d < 48; d++) xt[(48 * h + d) * 64 + n] = round_bf16(o[d] / sum);
  }
  __syncthreads();
  gemm(P.wo + 96 * rank, CH, 96, [&](int n, int d, float v) { P.out[pixel(n) + 96 * rank + d] = __float2bfloat16(v); });
}

#define HO 6
#define HQ 6
#define HV 6
#define E0 5
#define E1 15
#define ET 3
#define XSL "11110022220000"
#define XD 11
#define MS 8
#define KF 2
#define LF 9
#define NB 4
#define LAG 3
#define RA 0
#define QP 0
#define X1P 0
#define VP 4
#define X2P 4
#define HF 4
#define OF 5
#define AP 10
__host__ __device__ constexpr int g0(int r) { return r < 5 ? 3 * r : 16; }
__host__ __device__ constexpr int g1(int r) { return NB + (16 - NB) * r / 4; }
__host__ __device__ constexpr int xslot(int i) { return XSL[i] - '0'; }
__host__ __device__ constexpr int xbase(int i) { int b = 0; for (int q = 0; q < i; q++) b += xslot(q); return b; }
__host__ __device__ constexpr int xlast() { int l = 0; for (int q = 0; q < 14; q++) if (xslot(q)) l = q; return l; }
static_assert(xbase(14) == 12 && XD >= xlast(), "X schedule");

__global__ void __cluster_dims__(2, 1, 1) __launch_bounds__(THREADS, 1)
swin_attn_kernel(const __grid_constant__ CUtensorMap tm_x, const __grid_constant__ CUtensorMap tm_o, const __grid_constant__ CUtensorMap tm_w,
                 const __grid_constant__ CUtensorMap tm_wo, const __grid_constant__ Params P) {
  extern __shared__ __align__(1024) uint8_t smem_raw[];
  const uint32_t sbase = smem_u32(smem_raw);
  const int tid = threadIdx.x;
  {
    const uint32_t t = tid - 224;
    const uint32_t line = blockIdx.x + 128 * (t < 14 ? t : t < 19 ? t - 14 : 0);
    const uint8_t* base = reinterpret_cast<const uint8_t*>(t < 14 ? (const void*)P.wqkv : t < 19 ? (const void*)P.wo : (const void*)P.rp_idx);
    if (t < 20 && blockIdx.x < 128 && line < (t < 14 ? 1728u : 576u)) asm volatile("prefetch.global.L2 [%0];" ::"l"(base + line * 128) : "memory");
  }
  const int wid = uniform(tid >> 5);
  const int j = wid >> 2, warp = wid & 3;
  const uint32_t lane = tid & 31;
  uint32_t rank;
  asm("mov.u32 %0, %%cluster_ctarank;" : "=r"(rank));
  auto load_w = [&](int part) {
#pragma unroll
    for (int h = 0; h < 2; h++) {
      const uint32_t b = sbase + B_W + (part == 0 && h == 0 ? 32 : 8 * part);
      if (part == 0 || h == 0) mbar_expect_tx(b, part == 0 ? W_HALF : W_PART);
      if (part < 3) tma_load3(sbase + OFF_W + part * W_PART + h * W_HALF, &tm_w, 96 * h, (part == 0 ? 6 : part == 1 ? 0 : 12) + 3 * rank, b);
      else tma_load3(sbase + WO + h * W_HALF, &tm_wo, 96 * (rank ^ h), 3 * rank, b);
    }
  };
  uint32_t tab[4] = {0, 0, 0, 0};
  if ((wid >> 1) == 2) {
    const uint32_t* tp = reinterpret_cast<const uint32_t*>(P.rpb) + 2 * (tid - 128) + rank;
#pragma unroll
    for (int i = 0; i < 4; i++)
      if (i < 3 || tid < 128 + 33) asm volatile("ld.global.nc.u32 %0, [%1];" : "=r"(tab[i]) : "l"(tp + 128 * i) : "memory");
    if (elect_one()) {
      const uint32_t b = sbase + OFF_BAR + 128 * (wid & 1);
#pragma unroll
      for (uint32_t o = B_TOKEN; o <= B_LFREE; o += 8) mbar_init(b + o, 4);
      if (wid == 4) {
        mbar_arrive4(b + B_TOKEN);
        mbar_arrive4(b + B_KFREE);
        mbar_arrive4(b + B_VFREE);
      } else {
        mbar_init(sbase + B_DONE, 8);
      }
      asm volatile("fence.mbarrier_init.release.cluster;" ::: "memory");
    }
  } else {
    if (elect_one()) {
      const uint32_t b0 = sbase + (j == 0 ? OFF_BAR + B_XFULL + 8 * warp : wid == 6 ? B_IDX : B_W);
      const uint32_t b1 = sbase + (j == 0 ? OFF_BAR + 128 + B_XFULL + 8 * warp : wid == 6 ? B_W + 8 : B_W + 32);
      const uint32_t b2 = sbase + (j == 0 ? OFF_BAR + 128 + B_X1 + 8 * warp : wid == 6 ? B_W + 16 : B_W + 24);
      mbar_init(b0, 1);
      mbar_init(b1, 1);
      mbar_init(b2, 1);
      if (j == 0) mbar_arrive(b1);
      fence_async_proxy();
      if (wid == 6) {
        mbar_expect_tx(sbase + B_IDX, 16384);
        bulk_load(sbase + WO, P.rp_idx, 16384, sbase + B_IDX);
      }
    }
  }
  __syncwarp();
  const Plan plan = P.plan[blockIdx.x >> 1];
  const int nk = plan.w4n >> 16, wbase = plan.wbase;
  auto window = [&](int k) { const int a = wbase + k * P.wstride; return a + (int)((uint32_t)(a * P.wskip) >> 20); };
  auto window_first = [&](int k) { return (int)(((k < 2 ? plan.w01 : k < 4 ? plan.w23 : plan.w4n) >> (16 * (k & 1))) & 0xffff); };
  int win = window_first(j);
  const uint8_t* mask_b = reinterpret_cast<const uint8_t*>(P.mask);
  const uint32_t quad_row = 32 * (warp >> 1) + 4 * (warp & 1);
  const uint8_t* mask_q0 = mask_b + quad_row * 128;
  MaskRows mr;
  if (j == 0) {
    mr = mask_load(mask_q0 + (size_t)win * 8192 + lane * 16);
    load_tile(sbase + OFF_X + warp * 6144, warp, win, true, sbase + OFF_BAR + B_XFULL + 8 * warp, &tm_x);
  }
  if (wid == 7 && elect_one()) load_w(0);
  if (sbase & 1023) __trap();
  const uint32_t bar = uniform(smem_u32(smem_raw) + OFF_BAR + (tid & 128)), bar_o = uniform(smem_u32(smem_raw) + OFF_BAR + ((tid & 128) ^ 128));
  const uint32_t xbar = uniform(smem_u32(smem_raw) + OFF_BAR + (tid & 128) + B_XFULL + 8 * ((tid >> 5) & 3));
  const uint32_t xbar_o = uniform(smem_u32(smem_raw) + OFF_BAR + ((tid & 128) ^ 128) + B_XFULL + 8 * ((tid >> 5) & 3));
  const uint32_t xdst = uniform(smem_u32(smem_raw) + OFF_X + ((tid >> 5) & 3) * 6144);
  const uint32_t x1off = j == 0 ? 0 : warp < 2 ? OFF_L + 12288 : WO + 16384 - 12288;
  auto loads = [&](int step) {
    if (j == 1) {
      if (QP == step && warp == 0 && elect_one()) load_w(1);
      if (X1P == step) load_tile(xdst + x1off, warp, win, true, xbar + B_X1, &tm_x);
      if (VP == step && warp == 2 && elect_one()) load_w(2);
      if (X2P == step) load_tile(xdst, warp, window_first(2), 2 < nk, xbar_o, &tm_x);
    }
  };
  asm volatile("st.shared.u32 [%0], %1;" ::"r"(sbase + OFF_FAIL + 4 * tid), "r"(0) : "memory");
  bool big = false;
  if ((wid >> 1) == 2) {
#pragma unroll
    for (int i = 0; i < 4; i++) {
      const float b0 = bf_lo(tab[i]) * LOG2E, b1 = bf_hi(tab[i]) * LOG2E;
      asm volatile("st.shared.u32 [%0], %1;" ::"r"(sbase + OFF_TAB + 4 * (tid - 128) + 256 * i), "r"(pack_bf16(ex2(b0), ex2(b1))) : "memory");
      big |= !(fabsf(b0) <= 60.f) | !(fabsf(b1) <= 60.f);
    }
  }
  uint32_t force = __syncthreads_or(big) ? BAD_SUM : 0u;
  asm volatile("barrier.cluster.arrive.relaxed.aligned;" ::: "memory");
  loads(0);
  const uint32_t sb_a = uniform((sbase & 0x3FFFF) >> 4);
  const uint64_t w4 = desc_base<512, 2>(sb_a), k4 = desc_base<UB>(sb_a), v4 = desc_base<1024>(sb_a);
  const uint32_t blk = 2 * warp + ((lane >> 3) & 1);
  uint32_t stk = sbase + OFF_K + blk * UB + (lane >> 4) * 128 + (lane & 7) * 16;
  uint32_t stv = sbase + OFF_V + (lane >> 4) * 1024 + blk * 128 + (lane & 7) * 16;
  uint32_t xaddr0 = xdst + (lane & 15) * 128 + (((lane >> 4) ^ (lane & 7)) << 4);
  const uint32_t peer = rank ^ 1;
  const uint32_t area = uniform(smem_u32(smem_raw) + OFF_L + (tid >> 5) * 3072);
  const uint32_t r_bar = uniform(mapa(bar, peer)), r_area = uniform(mapa(area, peer));
  uint32_t l16 = lane * 16;
  uint32_t out_res = area + (lane & 15) * 64 + (((lane >> 4) ^ ((lane >> 1) & 3)) << 4);
  const uint32_t rzero = uniform(P.zero + (tid >> 10));
  const uint64_t mq = reinterpret_cast<uint64_t>(mask_b) + (32 * ((tid >> 6) & 1) + 4 * ((tid >> 5) & 1)) * 128;
  const uint8_t* mask_q = reinterpret_cast<const uint8_t*>(((uint64_t)uniform((uint32_t)(mq >> 32)) << 32) | uniform((uint32_t)mq));

  sched_barrier(stk, rzero); sched_barrier(stv, rzero); sched_barrier(xaddr0, rzero); sched_barrier(out_res, rzero); sched_barrier(l16, rzero);
  uint32_t ra[6], rb[6];
#pragma unroll
  for (int q = 0; q < 6; q++) {
    ra[q] = r_area + l16 + q * 512;
    rb[q] = r_bar + (q < 3 ? B_EX0 : B_EX1) + (tid >> 10);
    sched_barrier(ra[q], rzero);
    sched_barrier(rb[q], rzero);
  }
  uint32_t xa[48], oo[48], eb0[16], eb1[16];
  auto fetch = [&](auto H) {
    constexpr int o = 24 + 12 * decltype(H)::v;
    const uint32_t addr = area + l16 + 1536 * decltype(H)::v;
    const uint4 x = lds128v(addr), y = lds128v(addr + 512), z = lds128v(addr + 1024);
    oo[o + 0] = x.x; oo[o + 1] = x.y; oo[o + 2] = x.z; oo[o + 3] = x.w; oo[o + 4] = y.x; oo[o + 5] = y.y; oo[o + 6] = y.z; oo[o + 7] = y.w;
    oo[o + 8] = z.x; oo[o + 9] = z.y; oo[o + 10] = z.z; oo[o + 11] = z.w;
  };
  auto store_out = [&](auto PP, float (&d)[48]) {
    constexpr int p = decltype(PP)::v;
    store_chunk<p>(((p & 1) ? (out_res ^ 32) : out_res) + (p >> 1) * 1024, d);
  };
  uint64_t streaming;
  asm("createpolicy.fractional.L2::evict_first.b64 %0, 1.0;" : "=l"(streaming));
  auto send_out = [&](int w, bool valid) {
    int row, col2;
    quad_origin(w, warp, valid, row, col2);
    if (elect_one()) tma_store5(&tm_o, row, col2, 3 * rank, area, streaming);
    asm volatile("cp.async.bulk.commit_group;" ::: "memory");
  };
  auto prefetch_mask = [&](int w) {
    if (elect_one()) prefetch_l2(mask_b + (size_t)w * 8192 + (rank * 4 + warp) * 1024, 1024);
  };
  auto prefetch_x = [&](int w) {
    const int row = (8 * (w >> 6) + 4 + 4 * rank + warp) & (IMG - 1), col = 8 * (w & 63) + 4;
    if (elect_one()) prefetch_l2(reinterpret_cast<const uint8_t*>(P.x) + (size_t)(row * IMG + col) * (CH * 2), (w & 63) == 63 ? 4 * CH * 2 : 8 * CH * 2);
  };

  auto first_x = [&]() {
    uint32_t xaddr[4], all = ~0u;
#pragma unroll
    for (int q = 0; q < 4; q++) xaddr[q] = (xaddr0 + x1off) ^ (q << 5);
    mbar_wait(xbar + j * B_X1, 0);
    static_for<12>([&](auto I) { read_x<decltype(I)::v>(xa, xaddr); all &= xa[4 * decltype(I)::v + 3]; });
    reads_done(all, sbase + OFF_DUMMY);
  };
  auto gather = [&]() {
    const uint32_t odd = (l16 >> 6) & 1;
    const uint32_t ia = sbase + WO + (quad_row + 8 * (l16 >> 7) + odd) * 256 + (l16 & 0x30) * 2;
    mbar_wait(sbase + B_IDX, 0);
#pragma unroll
    for (int i = 0; i < 4; i++) {
      const int t = i >> 1, b = 4 * (i & 1);
      const uint4 u0 = lds128(ia + t * 512 + (i & 1) * 128 + odd * 16), u1 = lds128(ia + t * 512 + (i & 1) * 128 + 16 - odd * 16);
      const uint32_t id[8] = {u0.x, u0.y, u0.z, u0.w, u1.x, u1.y, u1.z, u1.w};
      uint32_t v[8];
#pragma unroll
      for (int q = 0; q < 8; q++) v[q] = lds32(sbase + OFF_TAB + 4 * id[q]);
#pragma unroll
      for (int q = 0; q < 4; q++) {
        const uint32_t x = odd ? v[(2 * q) ^ 4] : v[2 * q], y = odd ? v[(2 * q + 1) ^ 4] : v[2 * q + 1];
        eb0[2 * (b + q) + t] = __byte_perm(x, y, 0x5410);
        eb1[2 * (b + q) + t] = __byte_perm(x, y, 0x7632);
      }
    }
  };
  gather();
#pragma unroll
  for (int i = 0; i < 16; i += 4) {
    asm volatile("{\n.reg .pred p;\nsetp.ne.u32 p, %4, 0;\n@p ld.shared.v4.u32 {%0,%1,%2,%3}, [%4];\n}\n" : "+r"(eb0[i]), "+r"(eb0[i + 1]), "+r"(eb0[i + 2]), "+r"(eb0[i + 3]) : "r"(rzero));
    asm volatile("{\n.reg .pred p;\nsetp.ne.u32 p, %4, 0;\n@p ld.shared.v4.u32 {%0,%1,%2,%3}, [%4];\n}\n" : "+r"(eb1[i]), "+r"(eb1[i + 1]), "+r"(eb1[i + 2]), "+r"(eb1[i + 3]) : "r"(rzero));
  }
  loads(1);
#pragma unroll
  for (int h = 0; h < 2; h++) {
    constexpr uint32_t HI = 0x3E553E55u, LO = 0x396E396Eu;
    const uint32_t a = sbase + WK + h * 16384 + tid * 16;
    uint4 v[5];
    if (h == 0) mbar_wait(sbase + B_W + 32, 0);
    else mbar_wait(sbase + B_W, 0);
#pragma unroll
    for (int i = 0; i < 4 + h; i++) v[i] = lds128(a + i * 4096);
    loads(2 + h);
#pragma unroll
    for (int i = 0; i < 4 + h; i++)
      sts128(a + i * 4096, make_uint4(hfma2(v[i].x, HI, hmul2(v[i].x, LO)), hfma2(v[i].y, HI, hmul2(v[i].y, LO)),
                                      hfma2(v[i].z, HI, hmul2(v[i].z, LO)), hfma2(v[i].w, HI, hmul2(v[i].w, LO))));
    if (h == 0 && j == 0) first_x();
  }
  fence_async_proxy();
  bool masked = false;
  if (j == 0) {
    pin_rows(mr);
    masked = __any_sync(0xffffffffu, mask_or(mr) != 0);
  }
  __syncthreads();
  if (j == 1) {
    loads(4);
    mr = mask_load(mask_q0 + (size_t)win * 8192 + lane * 16);
    first_x();
    loads(5);
    wg_barrier(1);
    if (2 < nk) prefetch_mask(window_first(2));
    if (3 < nk) prefetch_x(window_first(3));
    if (3 < nk) prefetch_mask(window_first(3));
    if (4 < nk) {
      prefetch_x(window_first(4));
      prefetch_mask(window_first(4));
    }
    if (warp == 3 && elect_one()) load_w(3);
    pin_rows(mr);
    masked = __any_sync(0xffffffffu, mask_or(mr) != 0);
  }

  uint32_t par = 0;
  auto sched = [&]() { sched_barrier(force, rzero); };
  int k = j, wprev = win, wnext = window_first(j + 2), wx = window_first(j + 3);
#pragma unroll
  for (int i = 0; i < 24; i++) oo[i] = 0;
  for (;;) {
    float ca[48], cb[48], s0[32], s1[32];
    uint32_t qf[24];
    const int wnn = window(k + 4);
    bool ex0, ex1, kfree;
    fence_regs(xa);
    if (k == j) {
      if (j == 1) mbar_wait(bar + B_TOKEN, 0);
      gemm_phase<WK, 0, false>(ca, xa, w4, rzero, [&](auto) {});
      cluster_wait();
      mbar_wait(sbase + B_W + 8, 0);
      gemm_phase<WQ, HF, false>(cb, xa, w4, rzero, [&](auto I) {
        constexpr int s = decltype(I)::v, p = s - (HF - 1);
        if constexpr (p == 0) { fence_regs(ca); mbar_wait(bar + B_KFREE, 0); }
        if constexpr (p >= 0 && p < 6) store_chunk<(p >= 0 && p < 6) ? p : 0>(stk + p * 256, ca);
      });
      mbar_wait(sbase + B_W + 16, 0);
      if (j == 1) mbar_wait(sbase + B_W + 24, 0);
    } else {
      auto exchange = [&](auto G) {
        constexpr int g = decltype(G)::v;
        if constexpr (g == E0 - ET) ex0 = mbar_test(bar + B_EX0, par ^ 1);
        if constexpr (g == E1 - ET) ex1 = mbar_test(bar + B_EX1, par ^ 1);
        if constexpr (g == E0) { if (!ex0) mbar_wait(bar + B_EX0, par ^ 1); fetch(IC<0>{}); }
        if constexpr (g == E1) { if (!ex1) mbar_wait(bar + B_EX1, par ^ 1); fetch(IC<1>{}); }
      };
      gemm_phase<WK, 0, false>(cb, xa, w4, rzero, [&](auto I) { exchange(I); });
      gemm_phase<WO, HO, false>(ca, oo, w4, rzero, [&](auto I) {
        constexpr int s = decltype(I)::v, p = s - (HO - 1);
        if constexpr (p == -2) kfree = mbar_test(bar + B_KFREE, par);
        if constexpr (p == 0) { fence_regs(cb); if (!kfree) mbar_wait(bar + B_KFREE, par); }
        if constexpr (p >= 0 && p < 6) store_chunk<(p >= 0 && p < 6) ? p : 0>(stk + p * 256, cb);
        exchange(IC<12 + s>{});
        if constexpr (s == OF) wg_fence();
      });
      gemm_phase<WQ, HQ, false>(cb, xa, w4, rzero, [&](auto I) {
        constexpr int s = decltype(I)::v, p = s - (HQ - 1);
        if constexpr (p == 0) { fence_regs(ca); }
        if constexpr (p >= 0 && p < 6) store_out(IC<(p >= 0 && p < 6) ? p : 0>{}, ca);
      });
    }
    gemm_phase<WV, HV, true>(ca, xa, w4, rzero, [&](auto I) {
      constexpr int s = decltype(I)::v, p = s - (HV - 1);
      if constexpr (s == IDLE) {
        if (k + 4 < nk && k != 0) {
          prefetch_mask(wnn);
          prefetch_x(wnn);
        }
        if (l16 == 0) {
          mbar_expect_tx(bar + B_EX0, 1536);
          mbar_expect_tx(bar + B_EX1, 1536);
        }
      }
      if constexpr (p == 0) { fence_regs(cb); }
      if constexpr (p == 0) {
#pragma unroll
        for (int i = 0; i < 24; i++) qf[i] = pack_bf16(cb[2 * i], cb[2 * i + 1]);
      }
    });
    fence_regs(qf);
    fence_async_proxy();
    wg_barrier(j);
    wg_fence();
    issue_s<0>(s0, qf, k4);
    const bool vfree = mbar_test(bar + B_VFREE, par), xfull = mbar_test(xbar, par ^ 1);
    issue_s<1>(s1, qf, k4);
    if (l16 == 0) mbar_arrive(bar_o + B_TOKEN);
    send_out(wprev, k != j);
    uint32_t xaddr[4];
#pragma unroll
    for (int q = 0; q < 4; q++) xaddr[q] = xaddr0 ^ (q << 5);
    auto side = [&](auto R) {
      constexpr int r = decltype(R)::v, c = xslot(r), b = xbase(r);
      if constexpr (r == KF) {
        wg_wait<0>();
        fence_regs(s1);
        fence_regs(qf);
        if (l16 == 0) mbar_arrive(bar_o + B_KFREE);
      }
      if constexpr (r == LF) {
        asm volatile("cp.async.bulk.wait_group.read 0;" ::: "memory");
        __syncwarp();
        if (l16 == 0) mbar_arrive_remote_relaxed(r_bar + B_LFREE);
      }
      if constexpr (b == 0 && c > 0) { if (!xfull) mbar_wait(xbar, par ^ 1); }
      if constexpr (r == MS) mr = mask_load(offset_ptr(mask_q + (size_t)(k + 2 < nk ? wnext : win) * 8192, l16));
      static_for<c>([&](auto J) { read_x<b + decltype(J)::v>(xa, xaddr); });
      if constexpr (r == XD) {
        uint32_t all = ~0u;
#pragma unroll
        for (int i = 12 - xslot(xlast()); i < 12; i++) all &= xa[4 * i + 3];
        reads_done(all, sbase + OFF_DUMMY);
        load_tile(xdst, warp, wx, k + 3 < nk, xbar_o, &tm_x);
      }
    };
    auto store_v = [&](auto PP) { store_chunk<decltype(PP)::v>(stv + decltype(PP)::v * 2048, ca); };
    float o0[24], o1[24];
    uint32_t p0[16], p1[16], z0[6], z1[6], r0, r1;
    RowSums l0, l1;
    if (!vfree) mbar_wait(bar + B_VFREE, par);
    wg_wait<2>();
    fence_regs(ca);
    fence_regs(xa);
    store_v(IC<0>{});
    side(IC<0>{});
    store_v(IC<1>{});
    wg_wait<1>();
    fence_regs(s0);
    static_for<5>([&](auto R) {
      constexpr int r = decltype(R)::v;
      side(IC<1 + r>{});
      if constexpr (r == 0) {
        if (masked) {
          uint32_t l = l16;
          asm volatile("" : "+r"(l));
          const uint8_t* mp = offset_ptr(mask_q + (size_t)win * 8192, (l & 0x180) * 8 + (l & 0x40) * 2 + (l & 0x30));
          wg_wait<0>();
          fence_regs(s0);
          fence_regs(s1);
          const uint4 m[4] = {ldg128(mp), ldg128(mp + 64), ldg128(mp + 256), ldg128(mp + 320)};
          add_mask(s0, s1, m);
          if (__any_sync(0xffffffffu, force != 0)) {
            subtract_row_max(s0);
            subtract_row_max(s1);
          }
        }
      }
      if constexpr (r < 4) store_v(IC<(r < 4 ? r + 2 : 0)>{});
      exp_pairs<g0(r), g0(r + 1)>(s0);
      pack_pairs<(g0(r) > LAG ? g0(r) - LAG : 0), g0(r + 1) - LAG>(s0, eb0, p0, z0);
      sched();
    });
    fence_async_proxy();
    exp_pairs<0, NB>(s1);
    pack_pairs<16 - LAG, 16>(s0, eb0, p0, z0);
    pack_pairs<0, (NB > LAG ? NB - LAG : 0)>(s1, eb1, p1, z1);
    l0.start(z0);
    sched();
    wg_barrier(j);
    side(IC<6>{});
    wg_fence();
    issue_pv<0>(o0, p0, v4);
    sched();
    static_for<4>([&](auto R) {
      constexpr int r = decltype(R)::v;
      if constexpr (r == RA) r0 = l0.finish();
      side(IC<7 + r>{});
      exp_pairs<g1(r), g1(r + 1)>(s1);
      pack_pairs<(g1(r) > LAG ? g1(r) - LAG : 0), (r < 3 ? g1(r + 1) - LAG : 16)>(s1, eb1, p1, z1);
      if (r < 3) sched();
    });
    wg_fence();
    issue_pv<1>(o1, p1, v4);
    sched();
    l1.start(z1);
    side(IC<11>{});
    wg_wait<1>();
    fence_regs(o0);
    fence_regs(p0);
    uint32_t bad = normalize<0>(o0, r0, oo);
    mbar_wait(bar + B_LFREE, par);
#pragma unroll
    for (int q = 0; q < 3; q++) st_async16(ra[q], oo[4 * q], oo[4 * q + 1], oo[4 * q + 2], oo[4 * q + 3], rb[q]);
    sched();
    r1 = l1.finish();
    side(IC<12>{});
    wg_wait<0>();
    fence_regs(o1);
    fence_regs(p1);
    if (l16 == 0) mbar_arrive(bar_o + B_VFREE);
    bad = ((bad | normalize<1>(o1, r1, oo)) & BAD_SUM) | force;
#pragma unroll
    for (int q = 3; q < 6; q++) st_async16(ra[q], oo[4 * q], oo[4 * q + 1], oo[4 * q + 2], oo[4 * q + 3], rb[q]);
    sched();
    side(IC<13>{});
    pin_rows(mr);
    masked = __any_sync(0xffffffffu, (mask_or(mr) | bad) != 0);
    if (masked && __any_sync(0xffffffffu, (bad & BAD_SUM) != 0)) {
      force |= 1;
      if ((l16 >> 4) == (uint32_t)(k >> 6)) asm volatile("red.shared.or.b32 [%0], %1;" ::"r"(sbase + OFF_FAIL + 512 * j + 128 * warp + (l16 >> 2)), "r"(1u << ((k >> 1) & 31)) : "memory");
    }
    wprev = win;
    win = wnext;
    wnext = wnn;
    wx = window(k + 5);
    k += 2;
    if (k >= nk) break;
    par ^= 1;
    mbar_wait(bar + B_TOKEN, par);
  }
  {
    const uint32_t a = sbase + OFF_FAIL + 512 * j + 128 * warp + (l16 >> 2);
    st_async4(mapa(a + 1024, peer), lds32(a), mapa(sbase + B_DONE, peer));
    __syncwarp();
    if (l16 == 0) mbar_expect_tx(sbase + B_DONE, 128);
  }
  {
    float ca[48];
    mbar_wait(sbase + B_W + 24, 0);
    gemm_phase<WO, 0, false>(ca, oo, w4, rzero, [&](auto I) {
      constexpr int s = decltype(I)::v;
      if constexpr (s == 5) { mbar_wait(bar + B_EX0, par); fetch(IC<0>{}); wg_fence(); }
      if constexpr (s == 8) { mbar_wait(bar + B_EX1, par); fetch(IC<1>{}); wg_fence(); }
    });
    wg_wait<0>();
    fence_regs(ca);
    fence_regs(oo);
    static_for<6>([&](auto PP) { store_out(PP, ca); });
    fence_async_proxy();
    __syncwarp();
    send_out(wprev, true);
  }
  if (k == nk + 1) mbar_wait(xbar_o, j ? par : par ^ 1);
  mbar_wait(sbase + B_DONE, 0);
  uint32_t failed = 0;
#pragma unroll
  for (int i = 0; i < 4; i++) {
    const uint4 f = lds128(sbase + OFF_FAIL + 512 * i + l16);
    failed |= f.x | f.y | f.z | f.w;
  }
  if (__any_sync(0xffffffffu, failed != 0)) {
    asm volatile("cp.async.bulk.wait_group 0;" ::: "memory");
    asm volatile("fence.proxy.async;" ::: "memory");
    for (int kk = 0; kk < nk; kk++) {
      uint32_t f = 0;
      for (int i = 0; i < 8; i++) f |= lds32(sbase + OFF_FAIL + 1024 * (i >> 2) + 512 * (kk & 1) + 128 * (i & 3) + 4 * (kk >> 6));
      if ((f >> ((kk >> 1) & 31)) & 1) redo_window(P, reinterpret_cast<float*>(smem_raw), kk < 4 ? window_first(kk) : window(kk), rank);
    }
  }
  asm volatile("cp.async.bulk.wait_group.read 0;" ::: "memory");
}

typedef CUresult (*EncodeTiledFn)(CUtensorMap*, CUtensorMapDataType, cuuint32_t, void*, const cuuint64_t*, const cuuint64_t*,
                                  const cuuint32_t*, const cuuint32_t*, CUtensorMapInterleave, CUtensorMapSwizzle,
                                  CUtensorMapL2promotion, CUtensorMapFloatOOBfill);

void encode_image_map(EncodeTiledFn fn, CUtensorMap* tm, void* ptr, uint32_t group_c, CUtensorMapSwizzle sw) {
  const cuuint64_t dims[5] = {(cuuint64_t)group_c, 2, (cuuint64_t)IMG, (cuuint64_t)IMG / 2, (cuuint64_t)(CH / group_c)};
  const cuuint64_t strides[4] = {(cuuint64_t)CH * 2, (cuuint64_t)CH * 2 * IMG, (cuuint64_t)CH * 4, (cuuint64_t)group_c * 2};
  const cuuint32_t box[5] = {group_c, 2, 4, 2, 3};
  const cuuint32_t estr[5] = {1, 1, 1, 1, 1};
  fn(tm, CU_TENSOR_MAP_DATA_TYPE_BFLOAT16, 5, ptr, dims, strides, box, estr, CU_TENSOR_MAP_INTERLEAVE_NONE, sw,
     CU_TENSOR_MAP_L2_PROMOTION_L2_128B, CU_TENSOR_MAP_FLOAT_OOB_FILL_NONE);
}
void encode_weight_map(EncodeTiledFn fn, CUtensorMap* tm, void* ptr, uint32_t cols) {
  const cuuint64_t dims[3] = {32, (cuuint64_t)CH, (cuuint64_t)(cols / 32)};
  const cuuint64_t strides[2] = {(cuuint64_t)cols * 2, 64};
  const cuuint32_t box[3] = {32, 96, 3};
  const cuuint32_t estr[3] = {1, 1, 1};
  fn(tm, CU_TENSOR_MAP_DATA_TYPE_BFLOAT16, 3, ptr, dims, strides, box, estr, CU_TENSOR_MAP_INTERLEAVE_NONE, CU_TENSOR_MAP_SWIZZLE_64B,
     CU_TENSOR_MAP_L2_PROMOTION_L2_128B, CU_TENSOR_MAP_FLOAT_OOB_FILL_NONE);
}

}

extern "C" void kernel_launch(void* const* d_in, const int* in_sizes, int n_in, void* d_out, int out_size) {
  (void)in_sizes; (void)n_in; (void)out_size;
  static int nclusters = 0;
  static EncodeTiledFn encode = nullptr;
  if (nclusters == 0) {
    cudaFuncSetAttribute(swin_attn_kernel, cudaFuncAttributeMaxDynamicSharedMemorySize, SMEM_BYTES);
    int dev = 0, sms = 0;
    cudaGetDevice(&dev);
    cudaDeviceGetAttribute(&sms, cudaDevAttrMultiProcessorCount, dev);
    nclusters = sms / 2 < MAX_CLUSTERS ? sms / 2 : MAX_CLUSTERS;
    cudaLaunchConfig_t cfg = {};
    cfg.gridDim = dim3(2 * nclusters);
    cfg.blockDim = dim3(THREADS);
    cfg.dynamicSmemBytes = SMEM_BYTES;
    cudaLaunchAttribute at[1];
    at[0].id = cudaLaunchAttributeClusterDimension;
    at[0].val.clusterDim.x = 2; at[0].val.clusterDim.y = 1; at[0].val.clusterDim.z = 1;
    cfg.attrs = at; cfg.numAttrs = 1;
    int maxc = 0;
    if (cudaOccupancyMaxActiveClusters(&maxc, swin_attn_kernel, &cfg) == cudaSuccess && maxc > 0 && maxc < nclusters) nclusters = maxc;
    (void)cudaGetLastError();
    void* fn = nullptr;
    cudaDriverEntryPointQueryResult qres;
    cudaGetDriverEntryPoint("cuTensorMapEncodeTiled", &fn, cudaEnableDefault, &qres);
    encode = (EncodeTiledFn)fn;
  }
  CUtensorMap tm_x, tm_o, tm_w, tm_wo;
  encode_image_map(encode, &tm_x, d_in[0], 64, CU_TENSOR_MAP_SWIZZLE_128B);
  encode_image_map(encode, &tm_o, d_out, 32, CU_TENSOR_MAP_SWIZZLE_64B);
  encode_weight_map(encode, &tm_w, d_in[1], 3 * CH);
  encode_weight_map(encode, &tm_wo, d_in[2], CH);
  Params P;
  P.x = (const __nv_bfloat16*)d_in[0];
  P.wqkv = (const __nv_bfloat16*)d_in[1];
  P.wo = (const __nv_bfloat16*)d_in[2];
  P.rpb = (const __nv_bfloat16*)d_in[3];
  P.rp_idx = (const int*)d_in[4];
  P.mask = (const __nv_bfloat16*)d_in[5];
  P.out = (__nv_bfloat16*)d_out;
  P.wstride = nclusters;
  P.wskip = nclusters == 66 ? 16645 : 0;
  P.zero = 0;
  for (int b = 0; b < MAX_CLUSTERS; b++) {
    const bool special = P.wskip != 0;
    const int c = !special ? b : b < 4 ? AP + 8 * b : ((b - AP) & ~24) == 0 ? (b - AP) >> 3 : b;
    const int nspecial = c < 4 ? 0 : c < 7 ? 3 : 2, wbase = special ? c - 127 : c;
    uint32_t w[5];
    for (int k = 0; k < 5; k++) {
      const int v = k == 2 ? c - 4 : k == 3 ? c + 61 : 58 + c;
      const int u = (k >= 4 || !special) ? wbase + k * nclusters : k == 0 ? c : k == 1 ? (c < 4 ? 66 : 63) + c : 121 + 4 * k + c;
      w[k] = (k >= 4 || !special || k < 4 - nspecial) ? u + (special ? u / 63 : 0) : v < 64 ? 64 * v + 63 : 3968 + v;
    }
    P.plan[b] = {w[0] | w[1] << 16, w[2] | w[3] << 16, w[4] | (uint32_t)(NWIN / nclusters + (c < NWIN % nclusters)) << 16, wbase};
  }
  swin_attn_kernel<<<2 * nclusters, THREADS, SMEM_BYTES, cudaStreamPerThread>>>(tm_x, tm_o, tm_w, tm_wo, P);
}
```

```cpp
#include <cuda_runtime.h>
#include <cuda_bf16.h>
#include <cuda.h>
#include <stdint.h>

namespace {

constexpr int IMG = 512, CH = 192, NWIN = 4096;
constexpr int THREADS = 256;

constexpr uint32_t OFF_X = 0;
constexpr uint32_t OFF_K = 24576;
constexpr uint32_t UB = 1536;
constexpr uint32_t OFF_V = OFF_K + 12288;
constexpr uint32_t OFF_L = OFF_V + 12288;
constexpr uint32_t OFF_W = OFF_L + 2 * 12288;
constexpr uint32_t W_HALF = 3 * 96 * 64, W_PART = 2 * W_HALF;
constexpr uint32_t WK = OFF_W, WQ = OFF_W + W_PART, WV = OFF_W + 2 * W_PART, WO = OFF_W + 3 * W_PART;
constexpr uint32_t OFF_M = OFF_W + 4 * W_PART;
constexpr uint32_t OFF_BAR = OFF_M + 8192;
constexpr uint32_t B_XFULL = 0;
constexpr uint32_t B_TOKEN = 32;
constexpr uint32_t B_KFREE = 40, B_VFREE = 48;
constexpr uint32_t B_EX0 = 56, B_EX1 = 64;
constexpr uint32_t B_LFREE = 72;
constexpr uint32_t B_X1 = 80;
constexpr uint32_t B_W = OFF_BAR + 256;
constexpr uint32_t B_IDX = OFF_BAR + 296;
constexpr uint32_t B_DONE = OFF_BAR + 304;
constexpr uint32_t OFF_DUMMY = OFF_BAR + 320;
constexpr uint32_t OFF_FAIL = OFF_BAR + 384;
constexpr uint32_t B_MASK = OFF_FAIL + 2048;
constexpr uint32_t OFF_TAB = OFF_M;
constexpr uint32_t OFF_END = B_MASK + 64;
constexpr uint32_t SMEM_BYTES = OFF_END;

constexpr float LOG2E = 1.4426950408889634f;
constexpr float SCALE = 0.14433756729740643f;

__device__ __forceinline__ uint32_t smem_u32(const void* p) { return (uint32_t)__cvta_generic_to_shared(p); }
__device__ __forceinline__ void wg_fence() { asm volatile("wgmma.fence.sync.aligned;" ::: "memory"); }
__device__ __forceinline__ void wg_commit() { asm volatile("wgmma.commit_group.sync.aligned;" ::: "memory"); }
template <int N> __device__ __forceinline__ void wg_wait() { asm volatile("wgmma.wait_group.sync.aligned %0;" ::"n"(N) : "memory"); }
template <int N> __device__ __forceinline__ void fence_regs(float (&d)[N]) {
#pragma unroll
  for (int i = 0; i < N; i++) asm volatile("" : "+f"(d[i])::"memory");
}
template <int N> __device__ __forceinline__ void fence_regs(uint32_t (&d)[N]) {
#pragma unroll
  for (int i = 0; i < N; i++) asm volatile("" : "+r"(d[i])::"memory");
}
__device__ __forceinline__ bool elect_one() {
  uint32_t pred;
  asm volatile("{\n.reg .pred p;\nelect.sync _|p, 0xffffffff;\nselp.u32 %0, 1, 0, p;\n}\n" : "=r"(pred));
  return pred != 0;
}
__device__ __forceinline__ uint32_t pack_bf16(float lo, float hi) {
  uint32_t r;
  asm("cvt.rn.bf16x2.f32 %0, %1, %2;" : "=r"(r) : "f"(hi), "f"(lo));
  return r;
}
__device__ __forceinline__ float bf_lo(uint32_t v) { return __uint_as_float(v << 16); }
__device__ __forceinline__ float bf_hi(uint32_t v) { return __uint_as_float(v & 0xffff0000u); }
__device__ __forceinline__ float ex2(float x) {
  float y;
  asm("ex2.approx.ftz.f32 %0, %1;" : "=f"(y) : "f"(x));
  return y;
}
__device__ __forceinline__ uint32_t hadd2(uint32_t a, uint32_t b) {
  uint32_t r;
  asm("add.rn.bf16x2 %0, %1, %2;" : "=r"(r) : "r"(a), "r"(b));
  return r;
}
__device__ __forceinline__ uint32_t hmul2(uint32_t a, uint32_t b) {
  uint32_t r;
  asm("mul.rn.bf16x2 %0, %1, %2;" : "=r"(r) : "r"(a), "r"(b));
  return r;
}
__device__ __forceinline__ uint32_t dup_lo(uint32_t a) {
  uint32_t r;
  asm("{\n.reg .b16 l, h;\nmov.b32 {l, h}, %1;\nmov.b32 %0, {l, l};\n}\n" : "=r"(r) : "r"(a));
  return r;
}
__device__ __forceinline__ uint32_t dup_hi(uint32_t a) {
  uint32_t r;
  asm("{\n.reg .b16 l, h;\nmov.b32 {l, h}, %1;\nmov.b32 %0, {h, h};\n}\n" : "=r"(r) : "r"(a));
  return r;
}
__device__ __forceinline__ float rcp_approx(float x) {
  float y;
  asm("rcp.approx.ftz.f32 %0, %1;" : "=f"(y) : "f"(x));
  return y;
}
__device__ __forceinline__ uint4 ldg128(const void* p) {
  uint4 v;
  asm volatile("ld.global.L1::evict_normal.v4.u32 {%0,%1,%2,%3}, [%4];" : "=r"(v.x), "=r"(v.y), "=r"(v.z), "=r"(v.w) : "l"(p) : "memory");
  return v;
}
__device__ __forceinline__ void prefetch_l2(const void* p, uint32_t bytes) {
  asm volatile("cp.async.bulk.prefetch.L2.global [%0], %1;" ::"l"(p), "r"(bytes) : "memory");
}
__device__ __forceinline__ uint4 lds128(uint32_t addr) {
  uint4 v;
  asm volatile("ld.shared.v4.u32 {%0,%1,%2,%3}, [%4];" : "=r"(v.x), "=r"(v.y), "=r"(v.z), "=r"(v.w) : "r"(addr) : "memory");
  return v;
}
__device__ __forceinline__ uint4 lds128v(uint32_t addr) {
  uint4 v;
  asm volatile("ld.volatile.shared.v4.u32 {%0,%1,%2,%3}, [%4];" : "=r"(v.x), "=r"(v.y), "=r"(v.z), "=r"(v.w) : "r"(addr) : "memory");
  return v;
}
__device__ __forceinline__ uint32_t lds32(uint32_t addr) {
  uint32_t v;
  asm volatile("ld.shared.u32 %0, [%1];" : "=r"(v) : "r"(addr) : "memory");
  return v;
}
__device__ __forceinline__ void stmatrix_x4(uint32_t addr, uint32_t a, uint32_t b, uint32_t c, uint32_t d) {
  asm volatile("stmatrix.sync.aligned.m8n8.x4.shared.b16 [%0], {%1,%2,%3,%4};" ::"r"(addr), "r"(a), "r"(b), "r"(c), "r"(d) : "memory");
}
__device__ __forceinline__ void ldmatrix_x4(uint32_t addr, uint32_t& a, uint32_t& b, uint32_t& c, uint32_t& d) {
  asm volatile("ldmatrix.sync.aligned.m8n8.x4.shared.b16 {%0,%1,%2,%3}, [%4];" : "=r"(a), "=r"(b), "=r"(c), "=r"(d) : "r"(addr) : "memory");
}
__device__ __forceinline__ void fence_async_proxy() {
  asm volatile("fence.proxy.async.shared::cta;" ::: "memory");
}
__device__ __forceinline__ void wg_barrier(int j) { asm volatile("bar.sync %0, 128;" ::"r"(1 + j) : "memory"); }
__device__ __forceinline__ void cluster_wait() { asm volatile("barrier.cluster.wait.acquire.aligned;" ::: "memory"); }
__device__ __forceinline__ uint32_t mapa(uint32_t a, uint32_t rank) {
  uint32_t o;
  asm("mapa.shared::cluster.u32 %0, %1, %2;" : "=r"(o) : "r"(a), "r"(rank));
  return o;
}
__device__ __forceinline__ void mbar_init(uint32_t a, uint32_t cnt) { asm volatile("mbarrier.init.shared::cta.b64 [%0], %1;" ::"r"(a), "r"(cnt) : "memory"); }
__device__ __forceinline__ void mbar_expect_tx(uint32_t a, uint32_t tx) {
  asm volatile("mbarrier.arrive.expect_tx.shared::cta.b64 _, [%0], %1;" ::"r"(a), "r"(tx) : "memory");
}
__device__ __forceinline__ void mbar_arrive(uint32_t a) { asm volatile("mbarrier.arrive.shared::cta.b64 _, [%0];" ::"r"(a) : "memory"); }
__device__ __forceinline__ void mbar_arrive4(uint32_t a) { asm volatile("mbarrier.arrive.shared::cta.b64 _, [%0], 4;" ::"r"(a) : "memory"); }
__device__ __forceinline__ uint32_t uniform(uint32_t v) { return __shfl_sync(0xffffffffu, v, 0); }
__device__ __forceinline__ void mbar_arrive_remote_relaxed(uint32_t a) {
  asm volatile("mbarrier.arrive.relaxed.cluster.shared::cluster.b64 _, [%0];" ::"r"(a) : "memory");
}
__device__ __forceinline__ void mbar_wait(uint32_t a, uint32_t parity) {
  asm volatile(
      "{\n.reg .pred p;\n.reg .u32 n;\n"
      "mbarrier.try_wait.parity.shared::cta.b64 p, [%0], %1;\n"
      "@p bra WAIT_DONE;\n"
      "mov.u32 n, 0;\n"
      "WAIT_LOOP:\n"
      "add.u32 n, n, 1;\n"
      "setp.gt.u32 p, n, 50000000;\n"
      "@p trap;\n"
      "mbarrier.try_wait.parity.shared::cta.b64 p, [%0], %1;\n"
      "@!p bra WAIT_LOOP;\n"
      "WAIT_DONE:\n}\n" ::"r"(a), "r"(parity) : "memory");
}
__device__ __forceinline__ bool mbar_test(uint32_t a, uint32_t parity) {
  uint32_t ok;
  asm volatile("{\n.reg .pred p;\nmbarrier.test_wait.parity.shared::cta.b64 p, [%1], %2;\nselp.u32 %0, 1, 0, p;\n}\n" : "=r"(ok) : "r"(a), "r"(parity) : "memory");
  return ok != 0;
}
__device__ __forceinline__ uint32_t hfma2(uint32_t a, uint32_t b, uint32_t c) {
  uint32_t r;
  asm("fma.rn.bf16x2 %0, %1, %2, %3;" : "=r"(r) : "r"(a), "r"(b), "r"(c));
  return r;
}
__device__ __forceinline__ void st_async16(uint32_t raddr, uint32_t a, uint32_t b, uint32_t c, uint32_t d, uint32_t rbar) {
  asm volatile("st.async.weak.shared::cluster.mbarrier::complete_tx::bytes.v4.b32 [%0], {%1,%2,%3,%4}, [%5];" ::"r"(raddr),
               "r"(a), "r"(b), "r"(c), "r"(d), "r"(rbar) : "memory");
}

__device__ __forceinline__ void st_async4(uint32_t raddr, uint32_t v, uint32_t rbar) {
  asm volatile("st.async.weak.shared::cluster.mbarrier::complete_tx::bytes.b32 [%0], %1, [%2];" ::"r"(raddr), "r"(v), "r"(rbar) : "memory");
}
__device__ __forceinline__ void sts128(uint32_t addr, uint4 v) {
  asm volatile("st.shared.v4.u32 [%0], {%1,%2,%3,%4};" ::"r"(addr), "r"(v.x), "r"(v.y), "r"(v.z), "r"(v.w) : "memory");
}
__device__ __forceinline__ void bulk_load(uint32_t dst, const void* src, uint32_t bytes, uint32_t bar) {
  asm volatile("cp.async.bulk.shared::cta.global.mbarrier::complete_tx::bytes [%0], [%1], %2, [%3];" ::"r"(dst), "l"(src),
               "r"(bytes), "r"(bar) : "memory");
}
__device__ __forceinline__ void tma_load3(uint32_t dst, const CUtensorMap* tm, int c1, int c2, uint32_t bar) {
  asm volatile("cp.async.bulk.tensor.3d.shared::cta.global.tile.mbarrier::complete_tx::bytes [%0], [%1, {0, %2, %3}], [%4];" ::"r"(dst),
               "l"(tm), "r"(c1), "r"(c2), "r"(bar) : "memory");
}
__device__ __forceinline__ void tma_load5(uint32_t dst, const CUtensorMap* tm, int c2, int c3, uint32_t bar) {
  asm volatile("cp.async.bulk.tensor.5d.shared::cta.global.tile.mbarrier::complete_tx::bytes [%0], [%1, {0, 0, %2, %3, 0}], [%4];" ::"r"(dst),
               "l"(tm), "r"(c2), "r"(c3), "r"(bar) : "memory");
}
__device__ __forceinline__ void tma_load5m(uint32_t dst, const CUtensorMap* tm, int c1, int c4, uint32_t bar) {
  asm volatile("cp.async.bulk.tensor.5d.shared::cta.global.tile.mbarrier::complete_tx::bytes [%0], [%1, {0, %2, 0, 0, %3}], [%4];" ::"r"(dst),
               "l"(tm), "r"(c1), "r"(c4), "r"(bar) : "memory");
}
__device__ __forceinline__ void tma_store5(const CUtensorMap* tm, int c2, int c3, int c4, uint32_t src, uint64_t policy) {
  asm volatile("cp.async.bulk.tensor.5d.global.shared::cta.tile.bulk_group.L2::cache_hint [%0, {0, 0, %1, %2, %3}], [%4], %5;" ::"l"(tm),
               "r"(c2), "r"(c3), "r"(c4), "r"(src), "l"(policy) : "memory");
}
__device__ __forceinline__ void sched_barrier(uint32_t& t, uint32_t zero) {
  asm volatile("{\n.reg .pred p;\nsetp.ne.u32 p, %1, 0;\n@p mov.u32 %0, %%clock;\n}\n" : "+r"(t) : "r"(zero) : "memory");
}

__device__ __forceinline__ void wgmma_n48_a(float (&d)[24], uint32_t a0, uint32_t a1, uint32_t a2, uint32_t a3, uint64_t db) {
  asm volatile("{\n.reg .pred p;\nsetp.ne.b32 p, 1, 0;\n"
      "wgmma.mma_async.sync.aligned.m64n48k16.f32.bf16.bf16 "
      "{%0,%1,%2,%3,%4,%5,%6,%7,%8,%9,%10,%11,%12,%13,%14,%15,"
      "%16,%17,%18,%19,%20,%21,%22,%23}, "
      "{%24,%25,%26,%27}, %28, p, 1, 1, 1;\n}\n"
      : "+f"(d[0]), "+f"(d[1]), "+f"(d[2]), "+f"(d[3]), "+f"(d[4]), "+f"(d[5]), "+f"(d[6]), "+f"(d[7]),
        "+f"(d[8]), "+f"(d[9]), "+f"(d[10]), "+f"(d[11]), "+f"(d[12]), "+f"(d[13]), "+f"(d[14]), "+f"(d[15]),
        "+f"(d[16]), "+f"(d[17]), "+f"(d[18]), "+f"(d[19]), "+f"(d[20]), "+f"(d[21]), "+f"(d[22]), "+f"(d[23])
      : "r"(a0), "r"(a1), "r"(a2), "r"(a3), "l"(db));
}
__device__ __forceinline__ void wgmma_n48_z(float (&d)[24], uint32_t a0, uint32_t a1, uint32_t a2, uint32_t a3, uint64_t db) {
  asm volatile("{\n.reg .pred p;\nsetp.ne.b32 p, 0, 0;\n"
      "wgmma.mma_async.sync.aligned.m64n48k16.f32.bf16.bf16 "
      "{%0,%1,%2,%3,%4,%5,%6,%7,%8,%9,%10,%11,%12,%13,%14,%15,"
      "%16,%17,%18,%19,%20,%21,%22,%23}, "
      "{%24,%25,%26,%27}, %28, p, 1, 1, 1;\n}\n"
      : "=f"(d[0]), "=f"(d[1]), "=f"(d[2]), "=f"(d[3]), "=f"(d[4]), "=f"(d[5]), "=f"(d[6]), "=f"(d[7]),
        "=f"(d[8]), "=f"(d[9]), "=f"(d[10]), "=f"(d[11]), "=f"(d[12]), "=f"(d[13]), "=f"(d[14]), "=f"(d[15]),
        "=f"(d[16]), "=f"(d[17]), "=f"(d[18]), "=f"(d[19]), "=f"(d[20]), "=f"(d[21]), "=f"(d[22]), "=f"(d[23])
      : "r"(a0), "r"(a1), "r"(a2), "r"(a3), "l"(db));
}
__device__ __forceinline__ void wgmma_n96_a(float (&d)[48], uint32_t a0, uint32_t a1, uint32_t a2, uint32_t a3, uint64_t db) {
  asm volatile("{\n.reg .pred p;\nsetp.ne.b32 p, 1, 0;\n"
      "wgmma.mma_async.sync.aligned.m64n96k16.f32.bf16.bf16 "
      "{%0,%1,%2,%3,%4,%5,%6,%7,%8,%9,%10,%11,%12,%13,%14,%15,"
      "%16,%17,%18,%19,%20,%21,%22,%23,%24,%25,%26,%27,%28,%29,%30,%31,"
      "%32,%33,%34,%35,%36,%37,%38,%39,%40,%41,%42,%43,%44,%45,%46,%47}, "
      "{%48,%49,%50,%51}, %52, p, 1, 1, 1;\n}\n"
      : "+f"(d[0]), "+f"(d[1]), "+f"(d[2]), "+f"(d[3]), "+f"(d[4]), "+f"(d[5]), "+f"(d[6]), "+f"(d[7]),
        "+f"(d[8]), "+f"(d[9]), "+f"(d[10]), "+f"(d[11]), "+f"(d[12]), "+f"(d[13]), "+f"(d[14]), "+f"(d[15]),
        "+f"(d[16]), "+f"(d[17]), "+f"(d[18]), "+f"(d[19]), "+f"(d[20]), "+f"(d[21]), "+f"(d[22]), "+f"(d[23]),
        "+f"(d[24]), "+f"(d[25]), "+f"(d[26]), "+f"(d[27]), "+f"(d[28]), "+f"(d[29]), "+f"(d[30]), "+f"(d[31]),
        "+f"(d[32]), "+f"(d[33]), "+f"(d[34]), "+f"(d[35]), "+f"(d[36]), "+f"(d[37]), "+f"(d[38]), "+f"(d[39]),
        "+f"(d[40]), "+f"(d[41]), "+f"(d[42]), "+f"(d[43]), "+f"(d[44]), "+f"(d[45]), "+f"(d[46]), "+f"(d[47])
      : "r"(a0), "r"(a1), "r"(a2), "r"(a3), "l"(db));
}
__device__ __forceinline__ void wgmma_n96_z(float (&d)[48], uint32_t a0, uint32_t a1, uint32_t a2, uint32_t a3, uint64_t db) {
  asm volatile("{\n.reg .pred p;\nsetp.ne.b32 p, 0, 0;\n"
      "wgmma.mma_async.sync.aligned.m64n96k16.f32.bf16.bf16 "
      "{%0,%1,%2,%3,%4,%5,%6,%7,%8,%9,%10,%11,%12,%13,%14,%15,"
      "%16,%17,%18,%19,%20,%21,%22,%23,%24,%25,%26,%27,%28,%29,%30,%31,"
      "%32,%33,%34,%35,%36,%37,%38,%39,%40,%41,%42,%43,%44,%45,%46,%47}, "
      "{%48,%49,%50,%51}, %52, p, 1, 1, 1;\n}\n"
      : "=f"(d[0]), "=f"(d[1]), "=f"(d[2]), "=f"(d[3]), "=f"(d[4]), "=f"(d[5]), "=f"(d[6]), "=f"(d[7]),
        "=f"(d[8]), "=f"(d[9]), "=f"(d[10]), "=f"(d[11]), "=f"(d[12]), "=f"(d[13]), "=f"(d[14]), "=f"(d[15]),
        "=f"(d[16]), "=f"(d[17]), "=f"(d[18]), "=f"(d[19]), "=f"(d[20]), "=f"(d[21]), "=f"(d[22]), "=f"(d[23]),
        "=f"(d[24]), "=f"(d[25]), "=f"(d[26]), "=f"(d[27]), "=f"(d[28]), "=f"(d[29]), "=f"(d[30]), "=f"(d[31]),
        "=f"(d[32]), "=f"(d[33]), "=f"(d[34]), "=f"(d[35]), "=f"(d[36]), "=f"(d[37]), "=f"(d[38]), "=f"(d[39]),
        "=f"(d[40]), "=f"(d[41]), "=f"(d[42]), "=f"(d[43]), "=f"(d[44]), "=f"(d[45]), "=f"(d[46]), "=f"(d[47])
      : "r"(a0), "r"(a1), "r"(a2), "r"(a3), "l"(db));
}
__device__ __forceinline__ void wgmma_n96_p(float (&d)[48], uint32_t a0, uint32_t a1, uint32_t a2, uint32_t a3, uint64_t db, uint32_t acc) {
  asm volatile("{\n.reg .pred p;\nsetp.ne.b32 p, %53, 0;\n"
      "wgmma.mma_async.sync.aligned.m64n96k16.f32.bf16.bf16 "
      "{%0,%1,%2,%3,%4,%5,%6,%7,%8,%9,%10,%11,%12,%13,%14,%15,"
      "%16,%17,%18,%19,%20,%21,%22,%23,%24,%25,%26,%27,%28,%29,%30,%31,"
      "%32,%33,%34,%35,%36,%37,%38,%39,%40,%41,%42,%43,%44,%45,%46,%47}, "
      "{%48,%49,%50,%51}, %52, p, 1, 1, 1;\n}\n"
      : "+f"(d[0]), "+f"(d[1]), "+f"(d[2]), "+f"(d[3]), "+f"(d[4]), "+f"(d[5]), "+f"(d[6]), "+f"(d[7]),
        "+f"(d[8]), "+f"(d[9]), "+f"(d[10]), "+f"(d[11]), "+f"(d[12]), "+f"(d[13]), "+f"(d[14]), "+f"(d[15]),
        "+f"(d[16]), "+f"(d[17]), "+f"(d[18]), "+f"(d[19]), "+f"(d[20]), "+f"(d[21]), "+f"(d[22]), "+f"(d[23]),
        "+f"(d[24]), "+f"(d[25]), "+f"(d[26]), "+f"(d[27]), "+f"(d[28]), "+f"(d[29]), "+f"(d[30]), "+f"(d[31]),
        "+f"(d[32]), "+f"(d[33]), "+f"(d[34]), "+f"(d[35]), "+f"(d[36]), "+f"(d[37]), "+f"(d[38]), "+f"(d[39]),
        "+f"(d[40]), "+f"(d[41]), "+f"(d[42]), "+f"(d[43]), "+f"(d[44]), "+f"(d[45]), "+f"(d[46]), "+f"(d[47])
      : "r"(a0), "r"(a1), "r"(a2), "r"(a3), "l"(db), "r"(acc));
}
__device__ __forceinline__ void wgmma_n64_a(float (&d)[32], uint32_t a0, uint32_t a1, uint32_t a2, uint32_t a3, uint64_t db) {
  asm volatile("{\n.reg .pred p;\nsetp.ne.b32 p, 1, 0;\n"
      "wgmma.mma_async.sync.aligned.m64n64k16.f32.bf16.bf16 "
      "{%0,%1,%2,%3,%4,%5,%6,%7,%8,%9,%10,%11,%12,%13,%14,%15,"
      "%16,%17,%18,%19,%20,%21,%22,%23,%24,%25,%26,%27,%28,%29,%30,%31}, "
      "{%32,%33,%34,%35}, %36, p, 1, 1, 0;\n}\n"
      : "+f"(d[0]), "+f"(d[1]), "+f"(d[2]), "+f"(d[3]), "+f"(d[4]), "+f"(d[5]), "+f"(d[6]), "+f"(d[7]),
        "+f"(d[8]), "+f"(d[9]), "+f"(d[10]), "+f"(d[11]), "+f"(d[12]), "+f"(d[13]), "+f"(d[14]), "+f"(d[15]),
        "+f"(d[16]), "+f"(d[17]), "+f"(d[18]), "+f"(d[19]), "+f"(d[20]), "+f"(d[21]), "+f"(d[22]), "+f"(d[23]),
        "+f"(d[24]), "+f"(d[25]), "+f"(d[26]), "+f"(d[27]), "+f"(d[28]), "+f"(d[29]), "+f"(d[30]), "+f"(d[31])
      : "r"(a0), "r"(a1), "r"(a2), "r"(a3), "l"(db));
}
__device__ __forceinline__ void wgmma_n64_z(float (&d)[32], uint32_t a0, uint32_t a1, uint32_t a2, uint32_t a3, uint64_t db) {
  asm volatile("{\n.reg .pred p;\nsetp.ne.b32 p, 0, 0;\n"
      "wgmma.mma_async.sync.aligned.m64n64k16.f32.bf16.bf16 "
      "{%0,%1,%2,%3,%4,%5,%6,%7,%8,%9,%10,%11,%12,%13,%14,%15,"
      "%16,%17,%18,%19,%20,%21,%22,%23,%24,%25,%26,%27,%28,%29,%30,%31}, "
      "{%32,%33,%34,%35}, %36, p, 1, 1, 0;\n}\n"
      : "=f"(d[0]), "=f"(d[1]), "=f"(d[2]), "=f"(d[3]), "=f"(d[4]), "=f"(d[5]), "=f"(d[6]), "=f"(d[7]),
        "=f"(d[8]), "=f"(d[9]), "=f"(d[10]), "=f"(d[11]), "=f"(d[12]), "=f"(d[13]), "=f"(d[14]), "=f"(d[15]),
        "=f"(d[16]), "=f"(d[17]), "=f"(d[18]), "=f"(d[19]), "=f"(d[20]), "=f"(d[21]), "=f"(d[22]), "=f"(d[23]),
        "=f"(d[24]), "=f"(d[25]), "=f"(d[26]), "=f"(d[27]), "=f"(d[28]), "=f"(d[29]), "=f"(d[30]), "=f"(d[31])
      : "r"(a0), "r"(a1), "r"(a2), "r"(a3), "l"(db));
}

template <uint32_t OFF, uint32_t LBO>
__device__ __forceinline__ uint64_t desc_at(uint64_t base) {
  return base + (uint64_t)((OFF >> 4) + ((LBO >> 4) << 16));
}
template <uint32_t SBO, uint32_t SWIZZLE = 0>
__device__ __forceinline__ uint64_t desc_base(uint32_t addr4) {
  return ((uint64_t)SWIZZLE << 62) | ((uint64_t)(SBO >> 4) << 32) | (uint64_t)addr4;
}
__device__ __forceinline__ uint64_t pin(uint64_t v) {
  asm volatile("" : "+l"(v));
  return v;
}
template <int I> struct IC { static constexpr int v = I; };
template <int N, class F> __device__ __forceinline__ void static_for(F&& f) {
  if constexpr (N > 0) { static_for<N - 1>(f); f(IC<N - 1>{}); }
}

__device__ __forceinline__ void quad_origin(int win, int w, bool valid, int& row, int& col2) {
  col2 = (4 * (win & 63) + 2 + 2 * (w & 1)) & (IMG / 2 - 1);
  row = (8 * (win >> 6) + 4 + 4 * (w >> 1)) & (IMG - 1);
  if (!valid) row = IMG;
}
__device__ __forceinline__ void load_tile(uint32_t dst, int warp, int win, bool valid, uint32_t xbar, const CUtensorMap* tm_x) {
  int row, col2;
  quad_origin(win, warp, valid, row, col2);
  if (elect_one()) {
    mbar_expect_tx(xbar, 6144);
    tma_load5(dst, tm_x, row, col2, xbar);
  }
}
template <int S>
__device__ __forceinline__ void read_x(uint32_t (&xa)[48], const uint32_t (&xaddr)[4]) {
  ldmatrix_x4(xaddr[S & 3] + (S >> 2) * 2048, xa[4 * S], xa[4 * S + 1], xa[4 * S + 2], xa[4 * S + 3]);
}
__device__ __forceinline__ void reads_done(uint32_t last, uint32_t dummy_addr) {
  asm volatile("{\n.reg .pred p;\nsetp.eq.u32 p, %0, 0x7fc1fc17;\n@p st.shared.u32 [%1], %0;\n}\n" ::"r"(last), "r"(dummy_addr) : "memory");
}
template <int P>
__device__ __forceinline__ void store_chunk(uint32_t addr, float (&d)[48]) {
  stmatrix_x4(addr, pack_bf16(d[8 * P + 0], d[8 * P + 1]), pack_bf16(d[8 * P + 2], d[8 * P + 3]),
              pack_bf16(d[8 * P + 4], d[8 * P + 5]), pack_bf16(d[8 * P + 6], d[8 * P + 7]));
}
constexpr int IDLE = -100;
template <uint32_t WOFF, int H, bool TIED, class F>
__device__ __forceinline__ void gemm_phase(float (&run)[48], uint32_t (&x)[48], uint64_t w4, uint32_t rzero, F&& after) {
  wg_fence();
  static_for<12>([&](auto I) {
    constexpr int s = decltype(I)::v;
    const uint64_t d = desc_at<WOFF + (s / 6) * W_HALF + (s % 6) * 1024, 6144>(pin(w4));
    if constexpr (s == 0 && TIED) wgmma_n96_p(run, x[0], x[1], x[2], x[3], d, rzero);
    else if constexpr (s == 0) wgmma_n96_z(run, x[0], x[1], x[2], x[3], d);
    else wgmma_n96_a(run, x[4 * s], x[4 * s + 1], x[4 * s + 2], x[4 * s + 3], d);
    if constexpr (s == H - 1 || s == 11) wg_commit();
    if constexpr (s == H - 1) { after(IC<IDLE>{}); wg_wait<1>(); }
    after(I);
  });
}
template <int H>
__device__ __forceinline__ void issue_s(float (&s)[32], uint32_t (&q)[24], uint64_t k4_) {
  const uint64_t k4 = pin(k4_);
  static_for<3>([&](auto I) {
    constexpr int k = decltype(I)::v, i = 12 * H + 4 * k;
    const uint64_t d = desc_at<OFF_K + H * 768 + k * 256, 128>(k4);
    if constexpr (k == 0) wgmma_n64_z(s, q[i], q[i + 1], q[i + 2], q[i + 3], d);
    else wgmma_n64_a(s, q[i], q[i + 1], q[i + 2], q[i + 3], d);
  });
  wg_commit();
}
__device__ __forceinline__ const uint8_t* offset_ptr(const uint8_t* base, uint32_t off) {
  const uint8_t* r;
  asm volatile("{\n.reg .u64 o;\ncvt.u64.u32 o, %2;\nadd.u64 %0, %1, o;\n}\n" : "=l"(r) : "l"(base), "r"(off));
  return r;
}
struct MaskRows { uint4 a, b, c, d; };
__device__ __forceinline__ MaskRows mask_load(const uint8_t* mp) {
  MaskRows r;
  r.a = ldg128(mp); r.b = ldg128(mp + 1024); r.c = ldg128(mp + 2048); r.d = ldg128(mp + 3072);
  return r;
}
__device__ __forceinline__ void pin_rows(MaskRows& r) {
  asm volatile("" : "+r"(r.a.x), "+r"(r.a.y), "+r"(r.a.z), "+r"(r.a.w), "+r"(r.b.x), "+r"(r.b.y), "+r"(r.b.z), "+r"(r.b.w),
                    "+r"(r.c.x), "+r"(r.c.y), "+r"(r.c.z), "+r"(r.c.w), "+r"(r.d.x), "+r"(r.d.y), "+r"(r.d.z), "+r"(r.d.w)::"memory");
}
__device__ __forceinline__ uint32_t mask_or(const MaskRows& r) {
  return (r.a.x | r.a.y | r.a.z | r.a.w) | (r.b.x | r.b.y | r.b.z | r.b.w) | (r.c.x | r.c.y | r.c.z | r.c.w) | (r.d.x | r.d.y | r.d.z | r.d.w);
}
__device__ __forceinline__ void add_mask(float (&s0)[32], float (&s1)[32], const uint4 (&m)[4]) {
#pragma unroll
  for (int t = 0; t < 2; t++) {
#pragma unroll
    for (int b = 0; b < 8; b++) {
      const uint4 u = m[2 * t + (b >> 2)];
      const uint32_t v = (b & 3) == 0 ? u.x : (b & 3) == 1 ? u.y : (b & 3) == 2 ? u.z : u.w;
      const int i = 4 * b + 2 * t;
      s0[i] = fmaf(bf_lo(v), LOG2E, s0[i]); s0[i + 1] = fmaf(bf_hi(v), LOG2E, s0[i + 1]);
      s1[i] = fmaf(bf_lo(v), LOG2E, s1[i]); s1[i + 1] = fmaf(bf_hi(v), LOG2E, s1[i + 1]);
    }
  }
}
__device__ __forceinline__ void subtract_row_max(float (&s)[32]) {
#pragma unroll
  for (int t = 0; t < 2; t++) {
    float x = -INFINITY;
#pragma unroll
    for (int b = 0; b < 8; b++) x = fmaxf(x, fmaxf(s[4 * b + 2 * t], s[4 * b + 2 * t + 1]));
    x = fmaxf(x, __shfl_xor_sync(0xffffffffu, x, 1));
    x = fmaxf(x, __shfl_xor_sync(0xffffffffu, x, 2));
#pragma unroll
    for (int b = 0; b < 8; b++) { s[4 * b + 2 * t] -= x; s[4 * b + 2 * t + 1] -= x; }
  }
}
template <int I0, int I1>
__device__ __forceinline__ void exp_pairs(float (&s)[32]) {
#pragma unroll
  for (int i = 2 * I0; i < 2 * I1; i++) {
    asm volatile("" : "+f"(s[i])::"memory");
    s[i] = ex2(s[i]);
    asm volatile("" : "+f"(s[i])::"memory");
  }
}
template <int I0, int I1>
__device__ __forceinline__ void pack_pairs(float (&s)[32], const uint32_t (&eb)[16], uint32_t (&p)[16], uint32_t (&z)[6]) {
#pragma unroll
  for (int i = I0; i < I1; i++) {
    asm volatile("" : "+f"(s[2 * i]), "+f"(s[2 * i + 1])::"memory");
    p[i] = hmul2(pack_bf16(s[2 * i], s[2 * i + 1]), eb[i]);
    asm volatile("" : "+r"(p[i])::"memory");
    const int b = i >> 1, t = i & 1;
    if (b & 1) {
      uint32_t v = hadd2(p[i - 2], p[i]);
      if (b & 2) v = hadd2(z[4 + t], v);
      if (b == 7) v = hadd2(z[2 + t], v);
      uint32_t& dst = z[(b == 7 ? 0 : (b & 2) ? 2 : 4) + t];
      dst = v;
      asm volatile("" : "+r"(dst)::"memory");
    }
  }
}
struct RowSums {
  uint32_t a, b, c, d;
  __device__ __forceinline__ void start(const uint32_t (&z)[6]) {
    a = hadd2(__byte_perm(z[0], z[1], 0x5410), __byte_perm(z[0], z[1], 0x7632));
    b = __shfl_xor_sync(0xffffffffu, a, 1);
    c = __shfl_xor_sync(0xffffffffu, a, 2);
    d = __shfl_xor_sync(0xffffffffu, a, 3);
  }
  __device__ __forceinline__ uint32_t finish() {
    asm volatile("" : "+r"(a), "+r"(b), "+r"(c), "+r"(d)::"memory");
    const uint32_t x = hadd2(a, b), y = hadd2(c, d);
    return pack_bf16(rcp_approx(bf_lo(x) + bf_lo(y)), rcp_approx(bf_hi(x) + bf_hi(y)));
  }
};
template <int H>
__device__ __forceinline__ void issue_pv(float (&oacc)[24], uint32_t (&p)[16], uint64_t v4_) {
  const uint64_t v4 = pin(v4_);
  static_for<4>([&](auto I) {
    constexpr int k = decltype(I)::v;
    const uint64_t d = desc_at<OFF_V + H * 6144 + k * 256, 128>(v4);
    if constexpr (k == 0) wgmma_n48_z(oacc, p[0], p[1], p[2], p[3], d);
    else wgmma_n48_a(oacc, p[4 * k], p[4 * k + 1], p[4 * k + 2], p[4 * k + 3], d);
  });
  wg_commit();
}
constexpr uint32_t BAD_SUM = 0xE000E000u;
template <int H>
__device__ __forceinline__ uint32_t normalize(float (&oacc)[24], uint32_t r, uint32_t (&o)[48]) {
  const uint32_t ra = dup_lo(r), rb = dup_hi(r);
#pragma unroll
  for (int k = 0; k < 12; k++) o[12 * H + k] = hmul2(pack_bf16(oacc[2 * k], oacc[2 * k + 1]), (k & 1) ? rb : ra);
  return r - 0x2F802F80u;
}

constexpr int MAX_CLUSTERS = 72;
struct Plan { uint32_t w01, w23, w4n; int wbase; };
struct Params {
  const __nv_bfloat16 *x, *wqkv, *wo, *rpb;
  const int* rp_idx;
  const __nv_bfloat16* mask;
  __nv_bfloat16* out;
  int wstride, wskip, zero;
  __align__(16) Plan plan[MAX_CLUSTERS];
};
__device__ __forceinline__ float round_bf16(float v) { return __bfloat162float(__float2bfloat16(v)); }
__device__ __forceinline__ void redo_window(const Params& P, float* sm, int win, int rank) {
  float* xt = sm;
  float* qkv = sm + 192 * 64;
  const int tid = threadIdx.x;
  auto pixel = [&](int n) { return (size_t)(((8 * (win >> 6) + (n >> 3) + 4) & (IMG - 1)) * IMG + ((8 * (win & 63) + (n & 7) + 4) & (IMG - 1))) * CH; };
  auto gemm = [&](const __nv_bfloat16* w, int ldw, int ncols, auto&& put) {
    for (int e = tid; e < 4 * ncols; e += THREADS) {
      const int g = e / ncols, d = e - g * ncols;
      float acc[16];
#pragma unroll
      for (int i = 0; i < 16; i++) acc[i] = 0.f;
      for (int c = 0; c < CH; c++) {
        const float wv = __bfloat162float(w[c * ldw + d]);
#pragma unroll
        for (int i = 0; i < 16; i++) acc[i] = fmaf(xt[c * 64 + 16 * g + i], wv, acc[i]);
      }
#pragma unroll
      for (int i = 0; i < 16; i++) put(16 * g + i, d, acc[i]);
    }
  };
  __syncthreads();
  for (int e = tid; e < 64 * CH; e += THREADS) xt[(e % CH) * 64 + e / CH] = __bfloat162float(P.x[pixel(e / CH) + e % CH]);
  __syncthreads();
  gemm(P.wqkv, 3 * CH, 3 * CH, [&](int n, int d, float v) { qkv[n * 577 + d] = round_bf16(v); });
  __syncthreads();
  {
    const int n = tid & 63, h = tid >> 6;
    auto logit = [&](int m) {
      float s = 0.f;
      for (int d = 0; d < 48; d++) s = fmaf(qkv[n * 577 + 48 * h + d], qkv[m * 577 + CH + 48 * h + d], s);
      return s * SCALE + __bfloat162float(P.rpb[P.rp_idx[n * 64 + m] * 4 + h]) + __bfloat162float(P.mask[(size_t)win * 4096 + n * 64 + m]);
    };
    float mx = -INFINITY, sum = 0.f, o[48];
    for (int m = 0; m < 64; m++) mx = fmaxf(mx, logit(m));
#pragma unroll
    for (int d = 0; d < 48; d++) o[d] = 0.f;
    for (int m = 0; m < 64; m++) {
      const float p = expf(logit(m) - mx);
      sum += p;
#pragma unroll
      for (int d = 0; d < 48; d++) o[d] = fmaf(p, qkv[m * 577 + 2 * CH + 48 * h + d], o[d]);
    }
#pragma unroll
    for (int d = 0; d < 48; d++) xt[(48 * h + d) * 64 + n] = round_bf16(o[d] / sum);
  }
  __syncthreads();
  gemm(P.wo + 96 * rank, CH, 96, [&](int n, int d, float v) { P.out[pixel(n) + 96 * rank + d] = __float2bfloat16(v); });
}

#define HO 6
#define HQ 6
#define HV 6
#define E0 5
#define E1 15
#define ET 3
#define XSL "11110022220000"
#define XD 11
#define MS 8
#define KF 2
#define LF 9
#define NB 4
#define LAG 3
#define RA 0
#define QP 0
#define X1P 0
#define VP 4
#define X2P 4
#define HF 4
#define OF 5
#define AP 10
__host__ __device__ constexpr int g0(int r) { return r < 5 ? 3 * r : 16; }
__host__ __device__ constexpr int g1(int r) { return NB + (16 - NB) * r / 4; }
__host__ __device__ constexpr int xslot(int i) { return XSL[i] - '0'; }
__host__ __device__ constexpr int xbase(int i) { int b = 0; for (int q = 0; q < i; q++) b += xslot(q); return b; }
__host__ __device__ constexpr int xlast() { int l = 0; for (int q = 0; q < 14; q++) if (xslot(q)) l = q; return l; }
static_assert(xbase(14) == 12 && XD >= xlast(), "X schedule");

__global__ void __cluster_dims__(2, 1, 1) __launch_bounds__(THREADS, 1)
swin_attn_kernel(const __grid_constant__ CUtensorMap tm_x, const __grid_constant__ CUtensorMap tm_o, const __grid_constant__ CUtensorMap tm_w,
                 const __grid_constant__ CUtensorMap tm_wo, const __grid_constant__ CUtensorMap tm_m, const __grid_constant__ Params P) {
  extern __shared__ __align__(1024) uint8_t smem_raw[];
  const uint32_t sbase = smem_u32(smem_raw);
  const int tid = threadIdx.x;
  {
    const uint32_t t = tid - 224;
    const uint32_t line = blockIdx.x + 128 * (t < 14 ? t : t < 19 ? t - 14 : 0);
    const uint8_t* base = reinterpret_cast<const uint8_t*>(t < 14 ? (const void*)P.wqkv : t < 19 ? (const void*)P.wo : (const void*)P.rp_idx);
    if (t < 20 && blockIdx.x < 128 && line < (t < 14 ? 1728u : 576u)) asm volatile("prefetch.global.L2 [%0];" ::"l"(base + line * 128) : "memory");
  }
  const int wid = uniform(tid >> 5);
  const int j = wid >> 2, warp = wid & 3;
  const uint32_t lane = tid & 31;
  uint32_t rank;
  asm("mov.u32 %0, %%cluster_ctarank;" : "=r"(rank));
  auto load_w = [&](int part) {
#pragma unroll
    for (int h = 0; h < 2; h++) {
      const uint32_t b = sbase + B_W + (part == 0 && h == 0 ? 32 : 8 * part);
      if (part == 0 || h == 0) mbar_expect_tx(b, part == 0 ? W_HALF : W_PART);
      if (part < 3) tma_load3(sbase + OFF_W + part * W_PART + h * W_HALF, &tm_w, 96 * h, (part == 0 ? 6 : part == 1 ? 0 : 12) + 3 * rank, b);
      else tma_load3(sbase + WO + h * W_HALF, &tm_wo, 96 * (rank ^ h), 3 * rank, b);
    }
  };
  uint32_t tab[4] = {0, 0, 0, 0};
  if ((wid >> 1) == 2) {
    const uint32_t* tp = reinterpret_cast<const uint32_t*>(P.rpb) + 2 * (tid - 128) + rank;
#pragma unroll
    for (int i = 0; i < 4; i++)
      if (i < 3 || tid < 128 + 33) asm volatile("ld.global.nc.u32 %0, [%1];" : "=r"(tab[i]) : "l"(tp + 128 * i) : "memory");
    if (elect_one()) {
      const uint32_t b = sbase + OFF_BAR + 128 * (wid & 1);
#pragma unroll
      for (uint32_t o = B_TOKEN; o <= B_LFREE; o += 8) mbar_init(b + o, 4);
      if (wid == 4) {
        mbar_arrive4(b + B_TOKEN);
        mbar_arrive4(b + B_KFREE);
        mbar_arrive4(b + B_VFREE);
      } else {
        mbar_init(sbase + B_DONE, 8);
      }
      asm volatile("fence.mbarrier_init.release.cluster;" ::: "memory");
    }
  } else {
    if (elect_one()) {
      const uint32_t b0 = sbase + (j == 0 ? OFF_BAR + B_XFULL + 8 * warp : wid == 6 ? B_IDX : B_W);
      const uint32_t b1 = sbase + (j == 0 ? OFF_BAR + 128 + B_XFULL + 8 * warp : wid == 6 ? B_W + 8 : B_W + 32);
      const uint32_t b2 = sbase + (j == 0 ? OFF_BAR + 128 + B_X1 + 8 * warp : wid == 6 ? B_W + 16 : B_W + 24);
      mbar_init(b0, 1);
      mbar_init(b1, 1);
      mbar_init(b2, 1);
      if (j == 0) mbar_arrive(b1);
      fence_async_proxy();
      if (wid == 6) {
        mbar_expect_tx(sbase + B_IDX, 16384);
        bulk_load(sbase + WO, P.rp_idx, 16384, sbase + B_IDX);
      }
    }
  }
  __syncwarp();
  const Plan plan = P.plan[blockIdx.x >> 1];
  const int nk = plan.w4n >> 16, wbase = plan.wbase;
  auto window = [&](int k) { const int a = wbase + k * P.wstride; return a + (int)((uint32_t)(a * P.wskip) >> 20); };
  auto window_first = [&](int k) { return (int)(((k < 2 ? plan.w01 : k < 4 ? plan.w23 : plan.w4n) >> (16 * (k & 1))) & 0xffff); };
  int win = window_first(j);
  const uint8_t* mask_b = reinterpret_cast<const uint8_t*>(P.mask);
  const uint32_t quad_row = 32 * (warp >> 1) + 4 * (warp & 1);
  const uint8_t* mask_q0 = mask_b + quad_row * 128;
  MaskRows mr;
  if (j == 0) {
    mr = mask_load(mask_q0 + (size_t)win * 8192 + lane * 16);
    load_tile(sbase + OFF_X + warp * 6144, warp, win, true, sbase + OFF_BAR + B_XFULL + 8 * warp, &tm_x);
  }
  if (wid == 7 && elect_one()) load_w(0);
  if (sbase & 1023) __trap();
  const uint32_t bar = uniform(smem_u32(smem_raw) + OFF_BAR + (tid & 128)), bar_o = uniform(smem_u32(smem_raw) + OFF_BAR + ((tid & 128) ^ 128));
  const uint32_t xbar = uniform(smem_u32(smem_raw) + OFF_BAR + (tid & 128) + B_XFULL + 8 * ((tid >> 5) & 3));
  const uint32_t xbar_o = uniform(smem_u32(smem_raw) + OFF_BAR + ((tid & 128) ^ 128) + B_XFULL + 8 * ((tid >> 5) & 3));
  const uint32_t xdst = uniform(smem_u32(smem_raw) + OFF_X + ((tid >> 5) & 3) * 6144);
  const uint32_t x1off = j == 0 ? 0 : warp < 2 ? OFF_L + 12288 : WO + 16384 - 12288;
  auto loads = [&](int step) {
    if (j == 1) {
      if (QP == step && warp == 0 && elect_one()) load_w(1);
      if (X1P == step) load_tile(xdst + x1off, warp, win, true, xbar + B_X1, &tm_x);
      if (VP == step && warp == 2 && elect_one()) load_w(2);
      if (X2P == step) load_tile(xdst, warp, window_first(2), 2 < nk, xbar_o, &tm_x);
    }
  };
  asm volatile("st.shared.u32 [%0], %1;" ::"r"(sbase + OFF_FAIL + 4 * tid), "r"(0) : "memory");
  bool big = false;
  if ((wid >> 1) == 2) {
#pragma unroll
    for (int i = 0; i < 4; i++) {
      const float b0 = bf_lo(tab[i]) * LOG2E, b1 = bf_hi(tab[i]) * LOG2E;
      asm volatile("st.shared.u32 [%0], %1;" ::"r"(sbase + OFF_TAB + 4 * (tid - 128) + 256 * i), "r"(pack_bf16(ex2(b0), ex2(b1))) : "memory");
      big |= !(fabsf(b0) <= 60.f) | !(fabsf(b1) <= 60.f);
    }
  }
  uint32_t force = __syncthreads_or(big) ? BAD_SUM : 0u;
  asm volatile("barrier.cluster.arrive.relaxed.aligned;" ::: "memory");
  loads(0);
  const uint32_t sb_a = uniform((sbase & 0x3FFFF) >> 4);
  const uint64_t w4 = desc_base<512, 2>(sb_a), k4 = desc_base<UB>(sb_a), v4 = desc_base<1024>(sb_a);
  const uint32_t blk = 2 * warp + ((lane >> 3) & 1);
  uint32_t stk = sbase + OFF_K + blk * UB + (lane >> 4) * 128 + (lane & 7) * 16;
  uint32_t stv = sbase + OFF_V + (lane >> 4) * 1024 + blk * 128 + (lane & 7) * 16;
  uint32_t xaddr0 = xdst + (lane & 15) * 128 + (((lane >> 4) ^ (lane & 7)) << 4);
  const uint32_t peer = rank ^ 1;
  const uint32_t area = uniform(smem_u32(smem_raw) + OFF_L + (tid >> 5) * 3072);
  const uint32_t r_bar = uniform(mapa(bar, peer)), r_area = uniform(mapa(area, peer));
  uint32_t l16 = lane * 16;
  uint32_t out_res = area + (lane & 15) * 64 + (((lane >> 4) ^ ((lane >> 1) & 3)) << 4);
  const uint32_t rzero = uniform(P.zero + (tid >> 10));
  const uint64_t mq = reinterpret_cast<uint64_t>(mask_b) + (32 * ((tid >> 6) & 1) + 4 * ((tid >> 5) & 1)) * 128;
  const uint8_t* mask_q = reinterpret_cast<const uint8_t*>(((uint64_t)uniform((uint32_t)(mq >> 32)) << 32) | uniform((uint32_t)mq));

  sched_barrier(stk, rzero); sched_barrier(stv, rzero); sched_barrier(xaddr0, rzero); sched_barrier(out_res, rzero); sched_barrier(l16, rzero);
  uint32_t ra[6], rb[6];
#pragma unroll
  for (int q = 0; q < 6; q++) {
    ra[q] = r_area + l16 + q * 512;
    rb[q] = r_bar + (q < 3 ? B_EX0 : B_EX1) + (tid >> 10);
    sched_barrier(ra[q], rzero);
    sched_barrier(rb[q], rzero);
  }
  uint32_t xa[48], oo[48], eb0[16], eb1[16];
  auto fetch = [&](auto H) {
    constexpr int o = 24 + 12 * decltype(H)::v;
    const uint32_t addr = area + l16 + 1536 * decltype(H)::v;
    const uint4 x = lds128v(addr), y = lds128v(addr + 512), z = lds128v(addr + 1024);
    oo[o + 0] = x.x; oo[o + 1] = x.y; oo[o + 2] = x.z; oo[o + 3] = x.w; oo[o + 4] = y.x; oo[o + 5] = y.y; oo[o + 6] = y.z; oo[o + 7] = y.w;
    oo[o + 8] = z.x; oo[o + 9] = z.y; oo[o + 10] = z.z; oo[o + 11] = z.w;
  };
  auto store_out = [&](auto PP, float (&d)[48]) {
    constexpr int p = decltype(PP)::v;
    store_chunk<p>(((p & 1) ? (out_res ^ 32) : out_res) + (p >> 1) * 1024, d);
  };
  uint64_t streaming;
  asm("createpolicy.fractional.L2::evict_first.b64 %0, 1.0;" : "=l"(streaming));
  auto send_out = [&](int w, bool valid) {
    int row, col2;
    quad_origin(w, warp, valid, row, col2);
    if (elect_one()) tma_store5(&tm_o, row, col2, 3 * rank, area, streaming);
    asm volatile("cp.async.bulk.commit_group;" ::: "memory");
  };
  auto prefetch_mask = [&](int w) {
    if (elect_one()) prefetch_l2(mask_b + (size_t)w * 8192 + (rank * 4 + warp) * 1024, 1024);
  };
  auto prefetch_x = [&](int w) {
    const int row = (8 * (w >> 6) + 4 + 4 * rank + warp) & (IMG - 1), col = 8 * (w & 63) + 4;
    if (elect_one()) prefetch_l2(reinterpret_cast<const uint8_t*>(P.x) + (size_t)(row * IMG + col) * (CH * 2), (w & 63) == 63 ? 4 * CH * 2 : 8 * CH * 2);
  };

  auto first_x = [&]() {
    uint32_t xaddr[4], all = ~0u;
#pragma unroll
    for (int q = 0; q < 4; q++) xaddr[q] = (xaddr0 + x1off) ^ (q << 5);
    mbar_wait(xbar + j * B_X1, 0);
    static_for<12>([&](auto I) { read_x<decltype(I)::v>(xa, xaddr); all &= xa[4 * decltype(I)::v + 3]; });
    reads_done(all, sbase + OFF_DUMMY);
  };
  auto gather = [&]() {
    const uint32_t odd = (l16 >> 6) & 1;
    const uint32_t ia = sbase + WO + (quad_row + 8 * (l16 >> 7) + odd) * 256 + (l16 & 0x30) * 2;
    mbar_wait(sbase + B_IDX, 0);
#pragma unroll
    for (int i = 0; i < 4; i++) {
      const int t = i >> 1, b = 4 * (i & 1);
      const uint4 u0 = lds128(ia + t * 512 + (i & 1) * 128 + odd * 16), u1 = lds128(ia + t * 512 + (i & 1) * 128 + 16 - odd * 16);
      const uint32_t id[8] = {u0.x, u0.y, u0.z, u0.w, u1.x, u1.y, u1.z, u1.w};
      uint32_t v[8];
#pragma unroll
      for (int q = 0; q < 8; q++) v[q] = lds32(sbase + OFF_TAB + 4 * id[q]);
#pragma unroll
      for (int q = 0; q < 4; q++) {
        const uint32_t x = odd ? v[(2 * q) ^ 4] : v[2 * q], y = odd ? v[(2 * q + 1) ^ 4] : v[2 * q + 1];
        eb0[2 * (b + q) + t] = __byte_perm(x, y, 0x5410);
        eb1[2 * (b + q) + t] = __byte_perm(x, y, 0x7632);
      }
    }
  };
  gather();
#pragma unroll
  for (int i = 0; i < 16; i += 4) {
    asm volatile("{\n.reg .pred p;\nsetp.ne.u32 p, %4, 0;\n@p ld.shared.v4.u32 {%0,%1,%2,%3}, [%4];\n}\n" : "+r"(eb0[i]), "+r"(eb0[i + 1]), "+r"(eb0[i + 2]), "+r"(eb0[i + 3]) : "r"(rzero));
    asm volatile("{\n.reg .pred p;\nsetp.ne.u32 p, %4, 0;\n@p ld.shared.v4.u32 {%0,%1,%2,%3}, [%4];\n}\n" : "+r"(eb1[i]), "+r"(eb1[i + 1]), "+r"(eb1[i + 2]), "+r"(eb1[i + 3]) : "r"(rzero));
  }
  loads(1);
  if (elect_one()) mbar_init(sbase + B_MASK + 8 * wid, 1);
#pragma unroll
  for (int h = 0; h < 2; h++) {
    constexpr uint32_t HI = 0x3E553E55u, LO = 0x396E396Eu;
    const uint32_t a = sbase + WK + h * 16384 + tid * 16;
    uint4 v[5];
    if (h == 0) mbar_wait(sbase + B_W + 32, 0);
    else mbar_wait(sbase + B_W, 0);
#pragma unroll
    for (int i = 0; i < 4 + h; i++) v[i] = lds128(a + i * 4096);
    loads(2 + h);
#pragma unroll
    for (int i = 0; i < 4 + h; i++)
      sts128(a + i * 4096, make_uint4(hfma2(v[i].x, HI, hmul2(v[i].x, LO)), hfma2(v[i].y, HI, hmul2(v[i].y, LO)),
                                      hfma2(v[i].z, HI, hmul2(v[i].z, LO)), hfma2(v[i].w, HI, hmul2(v[i].w, LO))));
    if (h == 0 && j == 0) first_x();
  }
  fence_async_proxy();
  uint32_t masked = 0;
  if (j == 0) {
    pin_rows(mr);
    masked = __ballot_sync(0xffffffffu, mask_or(mr) != 0);
  }
  __syncthreads();
  if (j == 1) {
    loads(4);
    mr = mask_load(mask_q0 + (size_t)win * 8192 + lane * 16);
    first_x();
    loads(5);
    wg_barrier(1);
    if (2 < nk) prefetch_mask(window_first(2));
    if (3 < nk) prefetch_x(window_first(3));
    if (3 < nk) prefetch_mask(window_first(3));
    if (4 < nk) {
      prefetch_x(window_first(4));
      prefetch_mask(window_first(4));
    }
    if (warp == 3 && elect_one()) load_w(3);
    pin_rows(mr);
    masked = __ballot_sync(0xffffffffu, mask_or(mr) != 0);
  }

  uint32_t par = 0, mpar = 0;
  auto stage_mask = [&]() {
    if (masked && elect_one()) {
      mbar_expect_tx(sbase + B_MASK + 8 * wid, 2048);
      tma_load5m(sbase + OFF_M + 2048 * warp, &tm_m, 2 * (warp & 1), 4 * win + 2 * (warp >> 1), sbase + B_MASK + 8 * wid);
    }
  };
  auto sched = [&]() { sched_barrier(force, rzero); };
  int k = j, wprev = win, wnext = window_first(j + 2), wx = window_first(j + 3);
#pragma unroll
  for (int i = 0; i < 24; i++) oo[i] = 0;
  for (;;) {
    float ca[48], cb[48], s0[32], s1[32];
    uint32_t qf[24];
    const int wnn = window(k + 4);
    bool ex0, ex1, kfree;
    fence_regs(xa);
    if (k == j) {
      if (j == 1) mbar_wait(bar + B_TOKEN, 0);
      gemm_phase<WK, 0, false>(ca, xa, w4, rzero, [&](auto) {});
      cluster_wait();
      mbar_wait(sbase + B_W + 8, 0);
      gemm_phase<WQ, HF, false>(cb, xa, w4, rzero, [&](auto I) {
        constexpr int s = decltype(I)::v, p = s - (HF - 1);
        if constexpr (p == 0) { fence_regs(ca); mbar_wait(bar + B_KFREE, 0); stage_mask(); }
        if constexpr (p >= 0 && p < 6) store_chunk<(p >= 0 && p < 6) ? p : 0>(stk + p * 256, ca);
      });
      mbar_wait(sbase + B_W + 16, 0);
      if (j == 1) mbar_wait(sbase + B_W + 24, 0);
    } else {
      auto exchange = [&](auto G) {
        constexpr int g = decltype(G)::v;
        if constexpr (g == E0 - ET) ex0 = mbar_test(bar + B_EX0, par ^ 1);
        if constexpr (g == E1 - ET) ex1 = mbar_test(bar + B_EX1, par ^ 1);
        if constexpr (g == E0) { if (!ex0) mbar_wait(bar + B_EX0, par ^ 1); fetch(IC<0>{}); }
        if constexpr (g == E1) { if (!ex1) mbar_wait(bar + B_EX1, par ^ 1); fetch(IC<1>{}); }
      };
      gemm_phase<WK, 0, false>(cb, xa, w4, rzero, [&](auto I) { exchange(I); });
      gemm_phase<WO, HO, false>(ca, oo, w4, rzero, [&](auto I) {
        constexpr int s = decltype(I)::v, p = s - (HO - 1);
        if constexpr (p == -2) kfree = mbar_test(bar + B_KFREE, par);
        if constexpr (p == 0) {
          fence_regs(cb);
          if (!kfree || masked) { mbar_wait(bar + B_KFREE, par); stage_mask(); }
        }
        if constexpr (p >= 0 && p < 6) store_chunk<(p >= 0 && p < 6) ? p : 0>(stk + p * 256, cb);
        exchange(IC<12 + s>{});
        if constexpr (s == OF) wg_fence();
      });
      gemm_phase<WQ, HQ, false>(cb, xa, w4, rzero, [&](auto I) {
        constexpr int s = decltype(I)::v, p = s - (HQ - 1);
        if constexpr (p == 0) { fence_regs(ca); }
        if constexpr (p >= 0 && p < 6) store_out(IC<(p >= 0 && p < 6) ? p : 0>{}, ca);
      });
    }
    gemm_phase<WV, HV, true>(ca, xa, w4, rzero, [&](auto I) {
      constexpr int s = decltype(I)::v, p = s - (HV - 1);
      if constexpr (s == IDLE) {
        if (k + 4 < nk && k != 0) {
          prefetch_mask(wnn);
          prefetch_x(wnn);
        }
        if (l16 == 0) {
          mbar_expect_tx(bar + B_EX0, 1536);
          mbar_expect_tx(bar + B_EX1, 1536);
        }
      }
      if constexpr (p == 0) { fence_regs(cb); }
      if constexpr (p == 0) {
#pragma unroll
        for (int i = 0; i < 24; i++) qf[i] = pack_bf16(cb[2 * i], cb[2 * i + 1]);
      }
    });
    fence_regs(qf);
    fence_async_proxy();
    wg_barrier(j);
    wg_fence();
    issue_s<0>(s0, qf, k4);
    const bool vfree = mbar_test(bar + B_VFREE, par), xfull = mbar_test(xbar, par ^ 1);
    issue_s<1>(s1, qf, k4);
    if (l16 == 0) mbar_arrive(bar_o + B_TOKEN);
    send_out(wprev, k != j);
    uint32_t xaddr[4];
#pragma unroll
    for (int q = 0; q < 4; q++) xaddr[q] = xaddr0 ^ (q << 5);
    auto side = [&](auto R) {
      constexpr int r = decltype(R)::v, c = xslot(r), b = xbase(r);
      if constexpr (r == KF) {
        wg_wait<0>();
        fence_regs(s1);
        fence_regs(qf);
        if (l16 == 0) mbar_arrive(bar_o + B_KFREE);
      }
      if constexpr (r == LF) {
        asm volatile("cp.async.bulk.wait_group.read 0;" ::: "memory");
        __syncwarp();
        if (l16 == 0) mbar_arrive_remote_relaxed(r_bar + B_LFREE);
      }
      if constexpr (b == 0 && c > 0) { if (!xfull) mbar_wait(xbar, par ^ 1); }
      if constexpr (r == MS) mr = mask_load(offset_ptr(mask_q + (size_t)(k + 2 < nk ? wnext : win) * 8192, l16));
      static_for<c>([&](auto J) { read_x<b + decltype(J)::v>(xa, xaddr); });
      if constexpr (r == XD) {
        uint32_t all = ~0u;
#pragma unroll
        for (int i = 12 - xslot(xlast()); i < 12; i++) all &= xa[4 * i + 3];
        reads_done(all, sbase + OFF_DUMMY);
        load_tile(xdst, warp, wx, k + 3 < nk, xbar_o, &tm_x);
      }
    };
    auto store_v = [&](auto PP) { store_chunk<decltype(PP)::v>(stv + decltype(PP)::v * 2048, ca); };
    float o0[24], o1[24];
    uint32_t p0[16], p1[16], z0[6], z1[6], r0, r1;
    RowSums l0, l1;
    if (!vfree) mbar_wait(bar + B_VFREE, par);
    wg_wait<2>();
    fence_regs(ca);
    fence_regs(xa);
    store_v(IC<0>{});
    side(IC<0>{});
    store_v(IC<1>{});
    wg_wait<1>();
    fence_regs(s0);
    static_for<5>([&](auto R) {
      constexpr int r = decltype(R)::v;
      side(IC<1 + r>{});
      if constexpr (r == 0) {
        if (masked) {
          uint32_t l = l16;
          asm volatile("" : "+r"(l));
          l >>= 4;
          const uint32_t r0 = ((l >> 2) & 2) + (l & 4) + ((l >> 1) & 8), a0 = sbase + OFF_M + 2048 * warp + r0 * 128 + (((l & 3) ^ (r0 & 7)) << 4);
          mbar_wait(sbase + B_MASK + 8 * wid, mpar);
          mpar ^= 1;
          const uint4 m[4] = {lds128v(a0), lds128v(a0 ^ 64), lds128v((a0 + 128) ^ 16), lds128v((a0 + 128) ^ 80)};
          wg_wait<0>();
          fence_regs(s0);
          fence_regs(s1);
          add_mask(s0, s1, m);
          if (__any_sync(0xffffffffu, force != 0)) {
            subtract_row_max(s0);
            subtract_row_max(s1);
          }
        }
      }
      if constexpr (r < 4) store_v(IC<(r < 4 ? r + 2 : 0)>{});
      exp_pairs<g0(r), g0(r + 1)>(s0);
      pack_pairs<(g0(r) > LAG ? g0(r) - LAG : 0), g0(r + 1) - LAG>(s0, eb0, p0, z0);
      sched();
    });
    fence_async_proxy();
    exp_pairs<0, NB>(s1);
    pack_pairs<16 - LAG, 16>(s0, eb0, p0, z0);
    pack_pairs<0, (NB > LAG ? NB - LAG : 0)>(s1, eb1, p1, z1);
    l0.start(z0);
    sched();
    wg_barrier(j);
    side(IC<6>{});
    wg_fence();
    issue_pv<0>(o0, p0, v4);
    sched();
    static_for<4>([&](auto R) {
      constexpr int r = decltype(R)::v;
      if constexpr (r == RA) r0 = l0.finish();
      side(IC<7 + r>{});
      exp_pairs<g1(r), g1(r + 1)>(s1);
      pack_pairs<(g1(r) > LAG ? g1(r) - LAG : 0), (r < 3 ? g1(r + 1) - LAG : 16)>(s1, eb1, p1, z1);
      if (r < 3) sched();
    });
    wg_fence();
    issue_pv<1>(o1, p1, v4);
    sched();
    l1.start(z1);
    side(IC<11>{});
    wg_wait<1>();
    fence_regs(o0);
    fence_regs(p0);
    uint32_t bad = normalize<0>(o0, r0, oo);
    mbar_wait(bar + B_LFREE, par);
#pragma unroll
    for (int q = 0; q < 3; q++) st_async16(ra[q], oo[4 * q], oo[4 * q + 1], oo[4 * q + 2], oo[4 * q + 3], rb[q]);
    sched();
    r1 = l1.finish();
    side(IC<12>{});
    wg_wait<0>();
    fence_regs(o1);
    fence_regs(p1);
    if (l16 == 0) mbar_arrive(bar_o + B_VFREE);
    bad = ((bad | normalize<1>(o1, r1, oo)) & BAD_SUM) | force;
#pragma unroll
    for (int q = 3; q < 6; q++) st_async16(ra[q], oo[4 * q], oo[4 * q + 1], oo[4 * q + 2], oo[4 * q + 3], rb[q]);
    sched();
    side(IC<13>{});
    pin_rows(mr);
    masked = __ballot_sync(0xffffffffu, (mask_or(mr) | bad) != 0);
    if (masked && __any_sync(0xffffffffu, (bad & BAD_SUM) != 0)) {
      force |= 1;
      if (l16 == 0) asm volatile("red.shared.or.b32 [%0], %1;" ::"r"(sbase + OFF_FAIL + 128 * wid + 4 * (k >> 6)), "r"(1u << ((k >> 1) & 31)) : "memory");
    }
    wprev = win;
    win = wnext;
    wnext = wnn;
    wx = window(k + 5);
    k += 2;
    if (k >= nk) break;
    par ^= 1;
    mbar_wait(bar + B_TOKEN, par);
  }
  {
    __syncwarp();
    const uint32_t a = sbase + OFF_FAIL + 128 * wid + (l16 >> 2);
    st_async4(mapa(a + 1024, peer), lds32(a), mapa(sbase + B_DONE, peer));
    __syncwarp();
    if (l16 == 0) mbar_expect_tx(sbase + B_DONE, 128);
  }
  {
    float ca[48];
    mbar_wait(sbase + B_W + 24, 0);
    gemm_phase<WO, 0, false>(ca, oo, w4, rzero, [&](auto I) {
      constexpr int s = decltype(I)::v;
      if constexpr (s == 5) { mbar_wait(bar + B_EX0, par); fetch(IC<0>{}); wg_fence(); }
      if constexpr (s == 8) { mbar_wait(bar + B_EX1, par); fetch(IC<1>{}); wg_fence(); }
    });
    wg_wait<0>();
    fence_regs(ca);
    fence_regs(oo);
    static_for<6>([&](auto PP) { store_out(PP, ca); });
    fence_async_proxy();
    __syncwarp();
    send_out(wprev, true);
  }
  if (k == nk + 1) mbar_wait(xbar_o, j ? par : par ^ 1);
  mbar_wait(sbase + B_DONE, 0);
  uint32_t failed = 0;
#pragma unroll
  for (int i = 0; i < 4; i++) {
    const uint4 f = lds128(sbase + OFF_FAIL + 512 * i + l16);
    failed |= f.x | f.y | f.z | f.w;
  }
  if (__any_sync(0xffffffffu, failed != 0)) {
    asm volatile("cp.async.bulk.wait_group 0;" ::: "memory");
    asm volatile("fence.proxy.async;" ::: "memory");
    for (int kk = 0; kk < nk; kk++) {
      uint32_t f = 0;
      for (int i = 0; i < 8; i++) f |= lds32(sbase + OFF_FAIL + 1024 * (i >> 2) + 512 * (kk & 1) + 128 * (i & 3) + 4 * (kk >> 6));
      if ((f >> ((kk >> 1) & 31)) & 1) redo_window(P, reinterpret_cast<float*>(smem_raw), kk < 4 ? window_first(kk) : window(kk), rank);
    }
  }
  asm volatile("cp.async.bulk.wait_group.read 0;" ::: "memory");
}

typedef CUresult (*EncodeTiledFn)(CUtensorMap*, CUtensorMapDataType, cuuint32_t, void*, const cuuint64_t*, const cuuint64_t*,
                                  const cuuint32_t*, const cuuint32_t*, CUtensorMapInterleave, CUtensorMapSwizzle,
                                  CUtensorMapL2promotion, CUtensorMapFloatOOBfill);

void encode_image_map(EncodeTiledFn fn, CUtensorMap* tm, void* ptr, uint32_t group_c, CUtensorMapSwizzle sw) {
  const cuuint64_t dims[5] = {(cuuint64_t)group_c, 2, (cuuint64_t)IMG, (cuuint64_t)IMG / 2, (cuuint64_t)(CH / group_c)};
  const cuuint64_t strides[4] = {(cuuint64_t)CH * 2, (cuuint64_t)CH * 2 * IMG, (cuuint64_t)CH * 4, (cuuint64_t)group_c * 2};
  const cuuint32_t box[5] = {group_c, 2, 4, 2, 3};
  const cuuint32_t estr[5] = {1, 1, 1, 1, 1};
  fn(tm, CU_TENSOR_MAP_DATA_TYPE_BFLOAT16, 5, ptr, dims, strides, box, estr, CU_TENSOR_MAP_INTERLEAVE_NONE, sw,
     CU_TENSOR_MAP_L2_PROMOTION_L2_128B, CU_TENSOR_MAP_FLOAT_OOB_FILL_NONE);
}
void encode_weight_map(EncodeTiledFn fn, CUtensorMap* tm, void* ptr, uint32_t cols) {
  const cuuint64_t dims[3] = {32, (cuuint64_t)CH, (cuuint64_t)(cols / 32)};
  const cuuint64_t strides[2] = {(cuuint64_t)cols * 2, 64};
  const cuuint32_t box[3] = {32, 96, 3};
  const cuuint32_t estr[3] = {1, 1, 1};
  fn(tm, CU_TENSOR_MAP_DATA_TYPE_BFLOAT16, 3, ptr, dims, strides, box, estr, CU_TENSOR_MAP_INTERLEAVE_NONE, CU_TENSOR_MAP_SWIZZLE_64B,
     CU_TENSOR_MAP_L2_PROMOTION_L2_128B, CU_TENSOR_MAP_FLOAT_OOB_FILL_NONE);
}

void encode_mask_map(EncodeTiledFn fn, CUtensorMap* tm, void* ptr) {
  const cuuint64_t dims[5] = {64, 4, 2, 2, (cuuint64_t)NWIN * 4};
  const cuuint64_t strides[4] = {256, 1024, 128, 2048};
  const cuuint32_t box[5] = {64, 2, 2, 2, 2};
  const cuuint32_t estr[5] = {1, 1, 1, 1, 1};
  fn(tm, CU_TENSOR_MAP_DATA_TYPE_BFLOAT16, 5, ptr, dims, strides, box, estr, CU_TENSOR_MAP_INTERLEAVE_NONE, CU_TENSOR_MAP_SWIZZLE_128B,
     CU_TENSOR_MAP_L2_PROMOTION_L2_128B, CU_TENSOR_MAP_FLOAT_OOB_FILL_NONE);
}

}

extern "C" void kernel_launch(void* const* d_in, const int* in_sizes, int n_in, void* d_out, int out_size) {
  (void)in_sizes; (void)n_in; (void)out_size;
  static int nclusters = 0;
  static EncodeTiledFn encode = nullptr;
  if (nclusters == 0) {
    cudaFuncSetAttribute(swin_attn_kernel, cudaFuncAttributeMaxDynamicSharedMemorySize, SMEM_BYTES);
    int dev = 0, sms = 0;
    cudaGetDevice(&dev);
    cudaDeviceGetAttribute(&sms, cudaDevAttrMultiProcessorCount, dev);
    nclusters = sms / 2 < MAX_CLUSTERS ? sms / 2 : MAX_CLUSTERS;
    cudaLaunchConfig_t cfg = {};
    cfg.gridDim = dim3(2 * nclusters);
    cfg.blockDim = dim3(THREADS);
    cfg.dynamicSmemBytes = SMEM_BYTES;
    cudaLaunchAttribute at[1];
    at[0].id = cudaLaunchAttributeClusterDimension;
    at[0].val.clusterDim.x = 2; at[0].val.clusterDim.y = 1; at[0].val.clusterDim.z = 1;
    cfg.attrs = at; cfg.numAttrs = 1;
    int maxc = 0;
    if (cudaOccupancyMaxActiveClusters(&maxc, swin_attn_kernel, &cfg) == cudaSuccess && maxc > 0 && maxc < nclusters) nclusters = maxc;
    (void)cudaGetLastError();
    void* fn = nullptr;
    cudaDriverEntryPointQueryResult qres;
    cudaGetDriverEntryPoint("cuTensorMapEncodeTiled", &fn, cudaEnableDefault, &qres);
    encode = (EncodeTiledFn)fn;
  }
  CUtensorMap tm_x, tm_o, tm_w, tm_wo, tm_m;
  encode_mask_map(encode, &tm_m, d_in[5]);
  encode_image_map(encode, &tm_x, d_in[0], 64, CU_TENSOR_MAP_SWIZZLE_128B);
  encode_image_map(encode, &tm_o, d_out, 32, CU_TENSOR_MAP_SWIZZLE_64B);
  encode_weight_map(encode, &tm_w, d_in[1], 3 * CH);
  encode_weight_map(encode, &tm_wo, d_in[2], CH);
  Params P;
  P.x = (const __nv_bfloat16*)d_in[0];
  P.wqkv = (const __nv_bfloat16*)d_in[1];
  P.wo = (const __nv_bfloat16*)d_in[2];
  P.rpb = (const __nv_bfloat16*)d_in[3];
  P.rp_idx = (const int*)d_in[4];
  P.mask = (const __nv_bfloat16*)d_in[5];
  P.out = (__nv_bfloat16*)d_out;
  P.wstride = nclusters;
  P.wskip = nclusters == 66 ? 16645 : 0;
  P.zero = 0;
  for (int b = 0; b < MAX_CLUSTERS; b++) {
    const bool special = P.wskip != 0;
    const int c = !special ? b : b < 4 ? AP + 8 * b : ((b - AP) & ~24) == 0 ? (b - AP) >> 3 : b;
    const int nspecial = c < 4 ? 0 : c < 7 ? 3 : 2, wbase = special ? c - 127 : c;
    uint32_t w[5];
    for (int k = 0; k < 5; k++) {
      const int v = k == 2 ? c - 4 : k == 3 ? c + 61 : 58 + c;
      const int u = (k >= 4 || !special) ? wbase + k * nclusters : k == 0 ? c : k == 1 ? (c < 4 ? 66 : 63) + c : 121 + 4 * k + c;
      w[k] = (k >= 4 || !special || k < 4 - nspecial) ? u + (special ? u / 63 : 0) : v < 64 ? 64 * v + 63 : 3968 + v;
    }
    P.plan[b] = {w[0] | w[1] << 16, w[2] | w[3] << 16, w[4] | (uint32_t)(NWIN / nclusters + (c < NWIN % nclusters)) << 16, wbase};
  }
  swin_attn_kernel<<<2 * nclusters, THREADS, SMEM_BYTES, cudaStreamPerThread>>>(tm_x, tm_o, tm_w, tm_wo, tm_m, P);
}
```
